```python
import torch

def _softmax(x, axis=-1):
    return torch.softmax(x, dim=axis)
def _gelu(x):
    return torch.nn.functional.gelu(x, approximate="tanh")
def _silu(x):
    return torch.nn.functional.silu(x)
def _sigmoid(x):
    return torch.sigmoid(x)
def _layernorm(x, axis=-1, eps=1e-5):
    m = x.mean(dim=axis, keepdim=True)
    v = x.var(dim=axis, keepdim=True, unbiased=False)
    return (x - m) / torch.sqrt(v + eps)
def _scatter_add(tgt, idx, src, axis=0):
    return tgt.clone().index_add_(axis, idx, src)
def _segment_sum(src, seg, n):
    out = torch.zeros((n,) + src.shape[1:], dtype=src.dtype)
    return out.index_add_(0, seg, src)
def _pad(x, pw):
    flat = tuple(v for pair in reversed(pw) for v in pair)
    return torch.nn.functional.pad(x, flat)

kernel_name = 'interleave_layers__gqa_block_cached__glu_gated_reglu__decode'

def setup_inputs():

    _w = (lambda a: (lambda t: t.to(torch.bfloat16) if t.is_floating_point() else t)(torch.as_tensor(a)))
    def _A_setup():
        B, Sq, D = 1, 1, 512
        Hq, Hkv, Sk, Dh = 32, 8, 65536, 128
        assert Hq % Hkv == 0, (Hq, Hkv)
        return {
            "x": _w((lambda *s: torch.randn(*s, dtype=torch.bfloat16) * 0.05)(B, Sq, D)),
            "k_cache": _w((lambda *s: torch.randn(*s, dtype=torch.bfloat16) * 0.8)(B, Hkv, Sk, Dh)),
            "v_cache": _w((lambda *s: torch.randn(*s, dtype=torch.bfloat16) * 1.6)(B, Hkv, Sk, Dh)),
            "wq": _w((lambda *s: torch.randn(*s, dtype=torch.bfloat16) * 0.8)(D, Hq * Dh) * (D ** -0.5)),
            "wo": _w((lambda *s: torch.randn(*s, dtype=torch.bfloat16) * 1.6)(Hq * Dh, D) * ((Hq * Dh) ** -0.5)),
        }
    _A_in = _A_setup()

    def _B_setup():
        B, S, D, F = 1, 1, 512, 1792
        return {
            "x": _w((lambda *s: torch.randn(*s, dtype=torch.bfloat16) * 0.05)(B, S, D)),
            "W_gate": _w((lambda *s: torch.randn(*s, dtype=torch.bfloat16) * 0.2)(D, F) * (2.0 / D) ** 0.5),
            "W_up": _w((lambda *s: torch.randn(*s, dtype=torch.bfloat16) * 0.2)(D, F) * (2.0 / D) ** 0.5),
            "W_down": _w((lambda *s: torch.randn(*s, dtype=torch.bfloat16) * 0.2)(F, D) * (1.0 / F) ** 0.5),
        }
    _B_in = _B_setup()

    return {
        "A_x": _A_in["x"],
        "A_k_cache": _A_in["k_cache"],
        "A_v_cache": _A_in["v_cache"],
        "A_wq": _A_in["wq"],
        "A_wo": _A_in["wo"],
        "B_x": _B_in["x"],
        "B_W_gate": _B_in["W_gate"],
        "B_W_up": _B_in["W_up"],
        "B_W_down": _B_in["W_down"],
    }

def reference(A_x, A_k_cache, A_v_cache, A_wq, A_wo, B_x, B_W_gate, B_W_up, B_W_down):
    def _A_ref(x, k_cache, v_cache, wq, wo):
        B, Sq, D = x.shape
        Hq, Dh = 32, 128
        Hkv = k_cache.shape[1]
        rep = Hq // Hkv
        q = (lambda x, *d: x.permute(*d))((x @ wq).reshape(B, Sq, Hq, Dh), 0, 2, 1, 3)
        k = (lambda x, n, axis: torch.repeat_interleave(x, n, dim=axis))(k_cache, rep, axis=1)
        v = (lambda x, n, axis: torch.repeat_interleave(x, n, dim=axis))(v_cache, rep, axis=1)
        scores = torch.einsum("bhqd,bhkd->bhqk", q, k) * (Dh ** -0.5)
        p = _softmax(scores, axis=-1)
        o = torch.einsum("bhqk,bhkd->bhqd", p, v)
        return (lambda x, *d: x.permute(*d))(o, 0, 2, 1, 3).reshape(B, Sq, Hq * Dh) @ wo

    def _B_ref(x, W_gate, W_up, W_down):
        gate = torch.einsum("bsd,df->bsf", x, W_gate)
        up = torch.einsum("bsd,df->bsf", x, W_up)
        gate = gate * (lambda x, dt: x.to(dt))(gate > 0, gate.dtype)
        h = gate * up
        return torch.einsum("bsf,fd->bsd", h, W_down)

    x = A_x
    x = x + _A_ref(_layernorm(x, axis=-1), A_k_cache, A_v_cache, A_wq, A_wo)
    x = x + _B_ref(_layernorm(x, axis=-1), B_W_gate, B_W_up, B_W_down)
    x = x + _A_ref(_layernorm(x, axis=-1), A_k_cache, A_v_cache, A_wq, A_wo)
    x = x + _B_ref(_layernorm(x, axis=-1), B_W_gate, B_W_up, B_W_down)
    return x
```

```cpp
#include <cuda_runtime.h>
#include <cuda_bf16.h>
#include <cuda.h>
#include <stdint.h>

namespace {

constexpr int NCTA = 132, NWARP = 8, NTHR = 256;
constexpr int DM = 512, SK = 65536, FF = 1792;
constexpr int TILES_PER_HEAD = SK / 16;
constexpr int WPH = NCTA;
constexpr int NSLOT = 3;
constexpr int SLOT_BYTES = 8192;
constexpr int NREGT = 3;
#define KEEP_H 760
#define RESET_X 400
#define KVPROMO 0
#define THR_TAU 8
#define THR_GAIN 20
#define THR_MAX 0
#define KSTREAMS 2
#define START2 1
#define D2_UNTIL 1
#define WPF2 0
#define WO_R0 40
#define GU_RANK 0
#define KVPF 0
#define WO_AT 0
constexpr int T_DYN = 5 * 132;
constexpr int T_LAST = 4096 - 132;
constexpr int N_ALL = T_LAST - T_DYN;
constexpr int N_DYN = N_ALL - KEEP_H;
constexpr int KCAP = 16;
static_assert(KCAP * 132 > KEEP_H, "");

constexpr int SM_RING = 0;
constexpr int SM_W0 = NWARP * NSLOT * SLOT_BYTES;
constexpr int SM_BAR = SM_W0 + 32768;
constexpr int SM_STAT = SM_BAR + 384;
constexpr int SM_Q = SM_STAT + 128;
constexpr int Q_PITCH = 272;
constexpr int SM_LIST = SM_Q + 2 * 4 * Q_PITCH;
constexpr int SM_TOTAL = SM_LIST + NWARP * KCAP * 2;
constexpr int CS_HP = 152, CS_WP = 1024;

struct Scratch {
  uint32_t QX[2][2048];
  uint32_t PO[2][8][17][256];
  uint32_t ML[2][8][17][8];
  uint32_t Y1[2][8][512];
  uint32_t GU[2][2 * FF];
  uint32_t Y2[2][7][512];
  uint32_t cnt[2][32];
  uint32_t ctr[2][8][32];
};
__device__ __align__(1024) Scratch g_s;
#define TS(i) do {} while (0)

struct Maps { CUtensorMap k, v, wq, wo, wg, wu, wd; };

constexpr int SPIN_LIMIT = 1 << 22;

__device__ __forceinline__ void mbar_init(uint32_t bar, int cnt) {
  asm volatile("mbarrier.init.shared::cta.b64 [%0], %1;" ::"r"(bar), "r"(cnt) : "memory");
}
__device__ __forceinline__ void mbar_expect(uint32_t bar, uint32_t bytes) {
  asm volatile("mbarrier.arrive.expect_tx.shared::cta.b64 _, [%0], %1;" ::"r"(bar), "r"(bytes) : "memory");
}
__device__ __forceinline__ void mbar_wait(uint32_t bar, uint32_t parity) {
  uint32_t ok;
  int it = 0;
  do {
    asm volatile("{.reg .pred p; mbarrier.try_wait.parity.shared::cta.b64 p, [%1], %2; selp.u32 %0,1,0,p;}"
                 : "=r"(ok) : "r"(bar), "r"(parity) : "memory");
    if (++it > SPIN_LIMIT) __trap();
  } while (!__all_sync(0xffffffffu, ok));
}
__device__ __forceinline__ bool mbar_test(uint32_t bar, uint32_t parity) {
  uint32_t ok;
  asm volatile("{.reg .pred p; mbarrier.test_wait.parity.shared::cta.b64 p, [%1], %2; selp.u32 %0,1,0,p;}"
               : "=r"(ok) : "r"(bar), "r"(parity) : "memory");
  return ok != 0;
}
__device__ __forceinline__ int fresh_lane() { int l; asm volatile("mov.u32 %0, %laneid;" : "=r"(l)); return l; }
template <class T> __device__ __forceinline__ T* pin(T* p) { asm volatile("" : "+l"(p)); return p; }
__device__ __forceinline__ int opaque(int x) { asm volatile("" : "+r"(x)); return x; }
__device__ __forceinline__ void tma3d(uint32_t dst, const CUtensorMap* m, int row, uint32_t bar, uint64_t pol) {
  asm volatile("cp.async.bulk.tensor.3d.shared::cluster.global.mbarrier::complete_tx::bytes.L2::cache_hint"
               " [%0], [%1, {%3, %4, %3}], [%2], %5;"
               ::"r"(dst), "l"(m), "r"(bar), "r"(0), "r"(row), "l"(pol) : "memory");
}
__device__ __forceinline__ void tma2d(uint32_t dst, const CUtensorMap* m, int col, int row, uint32_t bar, uint64_t pol) {
  asm volatile("cp.async.bulk.tensor.2d.shared::cluster.global.mbarrier::complete_tx::bytes.L2::cache_hint"
               " [%0], [%1, {%3, %4}], [%2], %5;"
               ::"r"(dst), "l"(m), "r"(bar), "r"(col), "r"(row), "l"(pol) : "memory");
}
__device__ __forceinline__ void l2_prefetch(const void* p, uint32_t bytes) {
  asm volatile("cp.async.bulk.prefetch.L2.global [%0], %1;" ::"l"(p), "r"(bytes) : "memory");
}
__device__ __forceinline__ void tma3d_prefetch(const CUtensorMap* m, int row) {
  asm volatile("cp.async.bulk.prefetch.tensor.3d.L2.global [%0, {%1, %2, %1}];" ::"l"(m), "r"(0), "r"(row) : "memory");
}
#define KPF 0
__device__ __forceinline__ uint64_t pol_evict_first();
#define WPF 1
__device__ __forceinline__ void w_prefetch(const void* p, uint32_t bytes) {
  asm volatile("cp.async.bulk.prefetch.L2.global [%0], %1;" ::"l"(p), "r"(bytes) : "memory");
}
__device__ __forceinline__ void ef_prefetch(const void* p, uint32_t bytes) {
  asm volatile("cp.async.bulk.prefetch.L2.global.L2::cache_hint [%0], %1, %2;" ::"l"(p), "r"(bytes), "l"(pol_evict_first()) : "memory");
}
__device__ __forceinline__ uint64_t pol_evict_first() {
  uint64_t p;
  asm volatile("createpolicy.fractional.L2::evict_first.b64 %0, 1.0;" : "=l"(p));
  return p;
}
__device__ __forceinline__ void ldsm4(uint32_t& a, uint32_t& b, uint32_t& c, uint32_t& d, uint32_t addr) {
  asm volatile("ldmatrix.sync.aligned.m8n8.x4.shared.b16 {%0,%1,%2,%3}, [%4];"
               : "=r"(a), "=r"(b), "=r"(c), "=r"(d) : "r"(addr) : "memory");
}
__device__ __forceinline__ void ldsm4t(uint32_t& a, uint32_t& b, uint32_t& c, uint32_t& d, uint32_t addr) {
  asm volatile("ldmatrix.sync.aligned.m8n8.x4.trans.shared.b16 {%0,%1,%2,%3}, [%4];"
               : "=r"(a), "=r"(b), "=r"(c), "=r"(d) : "r"(addr) : "memory");
}
__device__ __forceinline__ void mma(float (&c)[4], uint32_t a0, uint32_t a1, uint32_t a2, uint32_t a3,
                                    uint32_t b0, uint32_t b1) {
  asm volatile("mma.sync.aligned.m16n8k16.row.col.f32.bf16.bf16.f32 {%0,%1,%2,%3}, {%4,%5,%6,%7}, {%8,%9}, {%0,%1,%2,%3};"
               : "+f"(c[0]), "+f"(c[1]), "+f"(c[2]), "+f"(c[3])
               : "r"(a0), "r"(a1), "r"(a2), "r"(a3), "r"(b0), "r"(b1));
}
__device__ __forceinline__ uint32_t movm(uint32_t a) {
  uint32_t d;
  asm volatile("movmatrix.sync.aligned.m8n8.trans.b16 %0, %1;" : "=r"(d) : "r"(a));
  return d;
}
__device__ __forceinline__ uint32_t pack2(float lo, float hi) {
  uint32_t d;
  asm("cvt.rn.bf16x2.f32 %0, %1, %2;" : "=r"(d) : "f"(hi), "f"(lo));
  return d;
}
__device__ __forceinline__ float lo16(uint32_t w) { return __uint_as_float(w << 16); }
__device__ __forceinline__ float hi16(uint32_t w) { return __uint_as_float(w & 0xffff0000u); }
__device__ __forceinline__ float rbf(float x) { return lo16(pack2(x, 0.f)); }
__device__ __forceinline__ float ex2(float x) {
  float y;
  asm("ex2.approx.ftz.f32 %0, %1;" : "=f"(y) : "f"(x));
  return y;
}
__device__ __forceinline__ uint32_t ldr32(const uint32_t* p) {
  uint32_t v;
  asm volatile("ld.relaxed.gpu.global.u32 %0, [%1];" : "=r"(v) : "l"(p) : "memory");
  return v;
}
__device__ __forceinline__ void ldr64(uint32_t& a, uint32_t& b, const uint32_t* p) {
  asm volatile("ld.relaxed.gpu.global.v2.u32 {%0,%1}, [%2];" : "=r"(a), "=r"(b) : "l"(p) : "memory");
}
__device__ __forceinline__ void str32(uint32_t* p, uint32_t v) {
  asm volatile("st.relaxed.gpu.global.u32 [%0], %1;" ::"l"(p), "r"(v) : "memory");
}
__device__ __forceinline__ void str64(uint32_t* p, uint32_t a, uint32_t b) {
  asm volatile("st.relaxed.gpu.global.v2.u32 [%0], {%1,%2};" ::"l"(p), "r"(a), "r"(b) : "memory");
}
__device__ __forceinline__ void sts32(uint32_t addr, uint32_t v) {
  asm volatile("st.shared.u32 [%0], %1;" ::"r"(addr), "r"(v) : "memory");
}
__device__ __forceinline__ void stsf(uint32_t addr, float v) {
  asm volatile("st.shared.f32 [%0], %1;" ::"r"(addr), "f"(v) : "memory");
}
__device__ __forceinline__ void stsf2(uint32_t addr, float a, float b) {
  asm volatile("st.shared.v2.f32 [%0], {%1,%2};" ::"r"(addr), "f"(a), "f"(b) : "memory");
}
__device__ __forceinline__ float ldsf(uint32_t addr) {
  float v;
  asm volatile("ld.shared.f32 %0, [%1];" : "=f"(v) : "r"(addr) : "memory");
  return v;
}
__device__ __forceinline__ void ldsf2(float& a, float& b, uint32_t addr) {
  asm volatile("ld.shared.v2.f32 {%0,%1}, [%2];" : "=f"(a), "=f"(b) : "r"(addr) : "memory");
}
__device__ __forceinline__ void fence_async() { asm volatile("fence.proxy.async.shared::cta;" ::: "memory"); }

constexpr float SCALE_C = 0.08838834764831845f * 1.4426950408889634f;

struct Attn {
  float o[4][4];
  float m0, m1, l0, l1;
};

__device__ __forceinline__ void softmax_step(Attn& st, const float (&s)[4], uint32_t& r0, uint32_t& r1) {
  float t0 = fmaxf(s[0], s[2]), t1 = fmaxf(s[1], s[3]);
#pragma unroll
  for (int o = 4; o <= 16; o <<= 1) {
    t0 = fmaxf(t0, __shfl_xor_sync(0xffffffffu, t0, o));
    t1 = fmaxf(t1, __shfl_xor_sync(0xffffffffu, t1, o));
  }
  float n0 = fmaxf(st.m0, t0 * SCALE_C), n1 = fmaxf(st.m1, t1 * SCALE_C);
  float a0 = ex2(st.m0 - n0), a1 = ex2(st.m1 - n1);
  st.m0 = n0; st.m1 = n1;
  float p0 = ex2(fmaf(s[0], SCALE_C, -n0)), p1 = ex2(fmaf(s[1], SCALE_C, -n1));
  float p2 = ex2(fmaf(s[2], SCALE_C, -n0)), p3 = ex2(fmaf(s[3], SCALE_C, -n1));
  r0 = movm(pack2(p0, p1));
  r1 = movm(pack2(p2, p3));
  st.l0 = fmaf(st.l0, a0, p0 + p2);
  st.l1 = fmaf(st.l1, a1, p1 + p3);
#pragma unroll
  for (int i = 0; i < 4; i++) {
    st.o[i][0] *= a0; st.o[i][1] *= a1; st.o[i][2] *= a0; st.o[i][3] *= a1;
  }
}

__device__ __forceinline__ void tile_smem(Attn& st, uint32_t kaddr, uint32_t vaddr, uint32_t qaddr, bool lowg) {
  float s[4] = {0.f, 0.f, 0.f, 0.f}, s2[4] = {0.f, 0.f, 0.f, 0.f};
#pragma unroll
  for (int j = 0; j < 4; j++) {
    uint32_t q0, q1, q2, q3, a0, a1, a2, a3, c0, c1, c2, c3;
    ldsm4(q0, q1, q2, q3, qaddr + j * 64);
    ldsm4(a0, a1, a2, a3, (kaddr ^ (((2 * j) & 3) << 5)) + (j >> 1) * 2048);
    ldsm4(c0, c1, c2, c3, (kaddr ^ (((2 * j + 1) & 3) << 5)) + (j >> 1) * 2048);
    mma(s, a0, a1, a2, a3, q0, q1);
    mma(s2, c0, c1, c2, c3, q2, q3);
  }
#pragma unroll
  for (int i = 0; i < 4; i++) s[i] += s2[i];
  uint32_t r0, r1;
  softmax_step(st, s, r0, r1);
#pragma unroll
  for (int kg = 0; kg < 2; kg++) {
    uint32_t r = kg ? r1 : r0;
    uint32_t b0 = lowg ? r : 0u, b1 = lowg ? 0u : r;
#pragma unroll
    for (int mt = 0; mt < 4; mt++) {
      uint32_t a0, a1, a2, a3;
      ldsm4t(a0, a1, a2, a3, (vaddr ^ (mt << 5)) + kg * 1024);
      mma(st.o[mt], a0, a1, a2, a3, b0, b1);
    }
  }
}

__device__ __forceinline__ void tile_load_regs(uint32_t (&f)[64], uint32_t kaddr, uint32_t vaddr) {
#pragma unroll
  for (int ks = 0; ks < 8; ks++)
    ldsm4(f[4 * ks], f[4 * ks + 1], f[4 * ks + 2], f[4 * ks + 3], (kaddr ^ ((ks & 3) << 5)) + (ks >> 2) * 2048);
#pragma unroll
  for (int i = 0; i < 8; i++)
    ldsm4t(f[32 + 4 * i], f[33 + 4 * i], f[34 + 4 * i], f[35 + 4 * i], (vaddr ^ ((i & 3) << 5)) + (i >> 2) * 1024);
}

__device__ __forceinline__ void tile_regs(Attn& st, const uint32_t (&f)[64], uint32_t qaddr, bool lowg) {
  float s[4] = {0.f, 0.f, 0.f, 0.f}, s2[4] = {0.f, 0.f, 0.f, 0.f};
#pragma unroll
  for (int j = 0; j < 4; j++) {
    uint32_t q0, q1, q2, q3;
    ldsm4(q0, q1, q2, q3, qaddr + j * 64);
    mma(s, f[8 * j], f[8 * j + 1], f[8 * j + 2], f[8 * j + 3], q0, q1);
    mma(s2, f[8 * j + 4], f[8 * j + 5], f[8 * j + 6], f[8 * j + 7], q2, q3);
  }
#pragma unroll
  for (int i = 0; i < 4; i++) s[i] += s2[i];
  uint32_t r0, r1;
  softmax_step(st, s, r0, r1);
#pragma unroll
  for (int kg = 0; kg < 2; kg++) {
    uint32_t r = kg ? r1 : r0;
    uint32_t b0 = lowg ? r : 0u, b1 = lowg ? 0u : r;
#pragma unroll
    for (int mt = 0; mt < 4; mt++) {
      const int i = 32 + 16 * kg + 4 * mt;
      mma(st.o[mt], f[i], f[i + 1], f[i + 2], f[i + 3], b0, b1);
    }
  }
}

template <int NKS, int KS0 = 0>
__device__ __forceinline__ void w_frags(uint32_t (&A)[32], uint32_t seg, int lane) {
  const int row = (lane & 7) + ((lane >> 4) << 3);
  const uint32_t base = seg + row * 64 + ((((lane >> 3) & 1) ^ ((row >> 1) & 3)) << 4);
#pragma unroll
  for (int i = 2 * KS0; i < 2 * NKS; i++)
    ldsm4t(A[4 * i], A[4 * i + 1], A[4 * i + 2], A[4 * i + 3], (base ^ ((i & 1) << 5)) + (i >> 1) * 1024);
}

template <int NKS, bool LN>
__device__ __forceinline__ float gemv_regs(const uint32_t (&A)[32], uint32_t sb, int warp, int lane, uint32_t xw) {
  float acc[2][4] = {{0.f, 0.f, 0.f, 0.f}, {0.f, 0.f, 0.f, 0.f}};
  const int t = lane & 3, g = lane >> 2;
  float s1 = lo16(xw) + hi16(xw), s2 = fmaf(lo16(xw), lo16(xw), hi16(xw) * hi16(xw));
#pragma unroll
  for (int ks = 0; ks < NKS; ks++) {
    const uint32_t x0 = __shfl_sync(0xffffffffu, xw, 8 * ks + t);
    const uint32_t x1 = __shfl_sync(0xffffffffu, xw, 8 * ks + 4 + t);
    const uint32_t b0 = (LN && (g & 1)) ? 0x3f803f80u : x0, b1 = (LN && (g & 1)) ? 0x3f803f80u : x1;
    mma(acc[0], A[8 * ks], A[8 * ks + 1], A[8 * ks + 2], A[8 * ks + 3], b0, b1);
    mma(acc[1], A[8 * ks + 4], A[8 * ks + 5], A[8 * ks + 6], A[8 * ks + 7], b0, b1);
    if (LN) {
      s1 += __shfl_xor_sync(0xffffffffu, s1, 16 >> ks);
      s2 += __shfl_xor_sync(0xffffffffu, s2, 16 >> ks);
    }
  }
  if (LN) {
    s1 += __shfl_xor_sync(0xffffffffu, s1, 1);
    s2 += __shfl_xor_sync(0xffffffffu, s2, 1);
  }
  const float v = (t & 2) ? ((t & 1) ? acc[1][2] : acc[1][0]) : ((t & 1) ? acc[0][2] : acc[0][0]);
  if (LN) {
    const float cs = (t & 2) ? ((t & 1) ? acc[1][3] : acc[1][1]) : ((t & 1) ? acc[0][3] : acc[0][1]);
    stsf2(sb + SM_Q + (warp * 32 + 8 * t + g) * 8, v, cs);
    if (lane == 0) stsf2(sb + SM_STAT + warp * 8, s2, s1);
  } else {
    stsf(sb + SM_Q + (warp * 32 + 8 * t + g) * 4, v);
  }
  __syncthreads();
  float y = 0.f;
  if (warp == 0) {
    if (LN) {
      float u[8], c[8], q[8], m[8];
#pragma unroll
      for (int w = 0; w < 8; w++) { ldsf2(q[w], m[w], sb + SM_STAT + w * 8); ldsf2(u[w], c[w], sb + SM_Q + (w * 32 + lane) * 8); }
      const float mean = (((m[0] + m[1]) + (m[2] + m[3])) + ((m[4] + m[5]) + (m[6] + m[7]))) * (1.f / 512.f);
      const float msq = (((q[0] + q[1]) + (q[2] + q[3])) + ((q[4] + q[5]) + (q[6] + q[7]))) * (1.f / 512.f);
      const float vb = rbf(fmaxf(fmaf(-mean, mean, msq), 0.f));
      float sq;
      asm("sqrt.approx.f32 %0, %1;" : "=f"(sq) : "f"(rbf(vb + 1e-5f)));
      y = ((u[0] + u[1]) + (u[2] + u[3])) + ((u[4] + u[5]) + (u[6] + u[7]));
      const float cs = ((c[0] + c[1]) + (c[2] + c[3])) + ((c[4] + c[5]) + (c[6] + c[7]));
      y = __fdividef(fmaf(-rbf(mean), cs, y), rbf(sq));
    } else {
      float u[8];
#pragma unroll
      for (int w = 0; w < 8; w++) u[w] = ldsf(sb + SM_Q + (w * 32 + lane) * 4);
      y = ((u[0] + u[1]) + (u[2] + u[3])) + ((u[4] + u[5]) + (u[6] + u[7]));
    }
  }
  return y;
}

template <int NP, class F, class G>
__device__ __forceinline__ uint32_t add_partials(const uint32_t* p, uint32_t xw, F side, G after) {
  uint32_t a[NP], b[NP];
#pragma unroll
  for (int k = 0; k < NP; k++) a[k] = b[k] = 0u;
  int it = 0;
  bool pend, done = false;
  do {
#pragma unroll
    for (int k = 0; k < NP; k++)
      if (a[k] == 0u || b[k] == 0u) ldr64(a[k], b[k], p + k * 512);
    if (!done) done = side();
    pend = false;
#pragma unroll
    for (int k = 0; k < NP; k++) pend |= (a[k] == 0u || b[k] == 0u);
    if (++it > SPIN_LIMIT) __trap();
  } while (__any_sync(0xffffffffu, pend) || !done);
  float y0 = 0.f, y1 = 0.f;
#pragma unroll
  for (int k = 0; k < NP; k++) { y0 += __uint_as_float(~a[k]); y1 += __uint_as_float(~b[k]); }
  asm volatile("" : "+f"(y0), "+f"(y1));
  after();
  return pack2(lo16(xw) + rbf(y0), hi16(xw) + rbf(y1));
}

__global__ void __launch_bounds__(NTHR, 1)
decode_kernel(const __grid_constant__ Maps maps, const uint32_t* __restrict__ x_in,
              const char* __restrict__ Kp, const char* __restrict__ Vp, const char* __restrict__ wq,
              const char* __restrict__ wo, const char* __restrict__ wg, const char* __restrict__ wu,
              const char* __restrict__ wd, uint32_t* __restrict__ out) {
  extern __shared__ __align__(1024) unsigned char smem[];
  const uint32_t sb = (uint32_t)__cvta_generic_to_shared(smem);
  const int tid = threadIdx.x, lane = tid & 31;
  const int warp = __shfl_sync(0xffffffffu, tid >> 5, 0);
  const int cta = blockIdx.x;
  const int gw = cta * NWARP + warp;
  const int head_lo = cta < 128 ? (cta & 7) : 2 * (cta - 128), head_hi = cta < 128 ? head_lo : head_lo + 1;
  const int head = warp < 4 ? head_lo : head_hi;
  const int jw = cta < 128 ? (cta >> 3) * 8 + warp : 128 + (warp & 3);
  const uint32_t ring = sb + SM_RING + warp * NSLOT * SLOT_BYTES;
  const uint32_t rbar = sb + SM_BAR + warp * NSLOT * 8;
  const uint32_t wbar = sb + SM_BAR + NWARP * NSLOT * 8 + warp * 16;
  const uint32_t wseg = sb + SM_W0 + warp * 4096;

  auto w_issue = [&](const CUtensorMap* m, int col, int row, bool lo, bool hi) {
    if (lane == 0) {
      const uint64_t pf = pol_evict_first();
      if (lo) { mbar_expect(wbar, 2048); tma2d(wseg, m, col, row, wbar, pf); }
      if (hi) { mbar_expect(wbar + 8, 2048); tma2d(wseg + 2048, m, col, row + 32, wbar + 8, pf); }
    }
  };

  auto issue = [&](int sl, int t, bool kp) {
    if (lane == 0) {
      const uint64_t pf = pol_evict_first();
      const int row = head * SK + t * 16;
      const uint32_t dst = ring + sl * SLOT_BYTES, b = rbar + sl * 8;
      mbar_expect(b, SLOT_BYTES);
      tma3d(dst, &maps.k, row, b, pf);
      if (kp) l2_prefetch(Kp + (size_t)row * 256, 4096);
      tma3d(dst + 4096, &maps.v, row, b, pf);
      if (kp) l2_prefetch(Vp + (size_t)row * 256, 4096);
    }
  };

  TS(0);
  uint32_t xw = __ldg(x_in + tid);
  if (lane == 0) {
    if (sb & 1023) __trap();
    if (gw < 1024) w_prefetch(wq + gw * 4096, 4096);
    mbar_init(wbar, 1); mbar_init(wbar + 8, 1);
#pragma unroll
    for (int i = 0; i < NSLOT; i++) mbar_init(rbar + i * 8, 1);
    asm volatile("fence.mbarrier_init.release.cluster;" ::: "memory");
    fence_async();
  }
  issue(0, jw, false);
  if (START2) issue(1, jw + WPH, false);
  if (tid == 32) {
    asm volatile("prefetch.tensormap [%0];" ::"l"(&maps.wq) : "memory");
    asm volatile("prefetch.tensormap [%0];" ::"l"(&maps.wo) : "memory");
    asm volatile("prefetch.tensormap [%0];" ::"l"(&maps.wg) : "memory");
    asm volatile("prefetch.tensormap [%0];" ::"l"(&maps.wu) : "memory");
    asm volatile("prefetch.tensormap [%0];" ::"l"(&maps.wd) : "memory");
  }
  __syncwarp();
  TS(21);

  auto koff_of = [](int l) -> uint32_t { return ((l & 7) + ((l >> 3) & 1) * 8) * 128 + (((l >> 4) ^ (l & 7)) << 4); };
  auto voff_of = [](int l) -> uint32_t { return 4096 + (l >> 4) * 2048 + (l & 7) * 128 + ((((l >> 3) & 1) ^ (l & 7)) << 4); };

  uint32_t f0[64], f1[64], f2[64];
#pragma unroll
  for (int i = 0; i < 64; i++) { f1[i] = 0; f2[i] = 0; }
  mbar_wait(rbar, 0);
  if (cta < 128) w_issue(&maps.wq, cta * 32, warp * 64, true, true);
  if (START2) issue(2, jw + 2 * WPH, false); else issue(1, jw + WPH, false);
  tile_load_regs(f0, ring + koff_of(lane), ring + voff_of(lane));

  uint32_t sst = 0;

  for (int layer = -1; layer < 2; layer++) {
    const bool live = layer >= 0;
    const int ly = live ? layer : 0;
    Attn st;
#pragma unroll
    for (int i = 0; i < 4; i++) { st.o[i][0] = st.o[i][1] = st.o[i][2] = st.o[i][3] = 0.f; }
    st.m0 = st.m1 = -INFINITY; st.l0 = st.l1 = 0.f;

    if (live) {
      const int ln = fresh_lane();
      const uint32_t koff = koff_of(ln), voff = voff_of(ln);
      const uint32_t qaddr = sb + SM_Q + ((head - head_lo) * 4 + (ln & 3)) * Q_PITCH + (ln >> 3) * 16;
      const bool lowg = ln < 16;
      int nxt = jw;
      if (layer == 0) sst = START2 ? 0x73 : 0x71;
      else sst = ((sst ^ 0x70) & 0x1f0070) | 7;
      int spin = 0;
      while (true) {
        int sl = -1;
        if ((sst & 2) && mbar_test(rbar + 8, (sst >> 5) & 1)) sl = 1;
        if ((sst & 1) && mbar_test(rbar, (sst >> 4) & 1)) sl = 0;
        if ((sst & 4) && mbar_test(rbar + 16, (sst >> 6) & 1)) sl = 2;
        sl = __shfl_sync(0xffffffffu, sl, 0);
        if (sl >= 0) {
          spin = 0;
          tile_smem(st, ring + sl * SLOT_BYTES + koff, ring + sl * SLOT_BYTES + voff, qaddr, lowg);
          __syncwarp();
          sst ^= 0x11u << sl;
          sst |= 0x4000;
          if (layer == 0 && sl == (START2 ? 1 : 0)) {
            if (!START2) { issue(1, jw + 4 * WPH, false); sst |= 2; }
          } else if (layer == 1 && sl != 2 && !(KSTREAMS == 3 && sl == 1 && (sst >> 16) >= D2_UNTIL)) {
            if ((sst >> 16) && (KSTREAMS == 2 || sl == 0)) {
              sst -= 1u << 16;
              uint32_t t;
              asm volatile("ld.shared.u16 %0, [%1];" : "=r"(t) : "r"(sb + SM_LIST + warp * (KCAP * 2) + (sst >> 16) * 2) : "memory");
              issue(sl, t, false); sst |= 1u << sl;
            }
          } else if (!(sst & 0x1000)) {
            const int d = __shfl_sync(0xffffffffu, nxt, 8);
            const int nd = layer == 0 ? N_ALL : N_DYN;
            if (d >= nd - RESET_X) sst |= 0x400;
            if (d < nd) {
              const bool kp = d >= N_DYN;
              const int ds = layer == 0 ? 2 : sl;
              issue(ds, T_DYN + d, kp); sst |= 1u << ds;
              if (kp) {
                if (lane == 0)
                  asm volatile("st.shared.u16 [%0], %1;" ::"r"(sb + SM_LIST + warp * (KCAP * 2) + (sst >> 16) * 2), "r"(T_DYN + d) : "memory");
                sst += 1u << 16;
              }
              if (layer == 0 && (sst >> 16) == KCAP) nxt = 1 << 20;
              else if (lane == 8) nxt = WPH + atomicAdd(&g_s.ctr[layer][head][0], 1u);
            } else {
              sst |= 0x1000;
              if (layer == 0) { issue(2, T_LAST + jw, false); sst |= 4; }
              if (WO_AT == 2 && lane == 0 && gw < 1024) w_prefetch(wo + opaque(gw) * 4096, 4096);
            }
          }
        } else if ((sst & 0x300) != 0x300) {
          if ((sst & 0x300) == 0) tile_regs(st, f0, qaddr, lowg);
          else if ((sst & 0x300) == 0x100) tile_regs(st, f1, qaddr, lowg);
          else tile_regs(st, f2, qaddr, lowg);
          sst += 0x100;
        } else if (warp == 7 && (sst & 0xc00) == 0x400) {
          sst = (sst | 0x800) & ~0x4000u;
          const int l_ = fresh_lane(), c_ = opaque(cta), y_ = opaque(ly);
          const uint4 z = make_uint4(0, 0, 0, 0);
          const int s_lo = c_ >> 3;
          uint4* po = reinterpret_cast<uint4*>(&g_s.PO[y_][head_lo][s_lo][0]);
          po[l_] = z; po[l_ + 32] = z;
          if (l_ < 2) reinterpret_cast<uint4*>(&g_s.ML[y_][head_lo][s_lo][0])[l_] = z;
          if (head_hi != head_lo) {
            po = reinterpret_cast<uint4*>(&g_s.PO[y_][head_hi][16][0]);
            po[l_] = z; po[l_ + 32] = z;
            if (l_ < 2) reinterpret_cast<uint4*>(&g_s.ML[y_][head_hi][16][0])[l_] = z;
          }
          if (c_ < 128) {
            (&g_s.Y1[y_][0][0])[c_ * 32 + l_] = 0;
            if (y_ == 0 && l_ < 16) g_s.QX[1][c_ * 16 + l_] = 0;
          }
          if (c_ < 112) { g_s.GU[y_][c_ * 32 + l_] = 0; (&g_s.Y2[y_][0][0])[c_ * 32 + l_] = 0; }
          if (c_ < 8 && y_ == 0 && l_ == 0) g_s.ctr[1][c_][0] = 0;
          __syncwarp();
          if (l_ == 0) {
            asm volatile("fence.acq_rel.gpu;" ::: "memory");
            const uint32_t old = atomicAdd(&g_s.cnt[y_][0], 1u);
            sts32(sb + SM_STAT + 64, (old / NCTA + 1) * NCTA);
          }
          __syncwarp();
        } else if ((sst & 7) == 0) {
          break;
        } else if ((sst & 0x6800) == 0x4800) {
          uint32_t target, c;
          asm volatile("ld.shared.u32 %0, [%1];" : "=r"(target) : "r"(sb + SM_STAT + 64) : "memory");
          asm volatile("ld.acquire.gpu.global.u32 %0, [%1];" : "=r"(c) : "l"(&g_s.cnt[opaque(ly)][0]) : "memory");
          sst &= ~0x4000u;
          if (__all_sync(0xffffffffu, (int)(c - target) >= 0)) sst |= 0x2000;
        } else if (++spin > SPIN_LIMIT) {
          __trap();
        }
      }
      TS(2 + 10 * layer);
      if (WO_AT == 0 && lane == 0 && gw < 1024) w_prefetch(wo + opaque(gw) * 4096, 4096);
      if (WO_AT == 3 && lane == 8) {
        const int r = (nxt - (layer == 0 ? N_ALL : N_DYN) - WO_R0) * 8 + head;
        if (r >= 0 && r < 512) w_prefetch(wo + r * 8192, 8192);
        else if (GU_RANK && r >= 512 && r < 512 + 224) w_prefetch(wg + (r - 512) * 8192, 8192);
        else if (GU_RANK && r >= 736 && r < 736 + 224) w_prefetch(wu + (r - 736) * 8192, 8192);
      }
    }

    if (live) {
#pragma unroll
      for (int o = 4; o <= 16; o <<= 1) {
        st.l0 += __shfl_xor_sync(0xffffffffu, st.l0, o);
        st.l1 += __shfl_xor_sync(0xffffffffu, st.l1, o);
      }
      const int g = lane >> 2, t = lane & 3;
      const uint32_t cs = sb + SM_W0 + warp * (CS_WP * 4);
      if (live) {
        const uint32_t a = cs + (((2 * t) & 3) * CS_HP + (t >> 1) * 72 + g) * 4;
#pragma unroll
        for (int mt = 0; mt < 4; mt++) {
          stsf(a + mt * 64, st.o[mt][0]);
          stsf(a + mt * 64 + CS_HP * 4, st.o[mt][1]);
          stsf(a + mt * 64 + 32, st.o[mt][2]);
          stsf(a + mt * 64 + 32 + CS_HP * 4, st.o[mt][3]);
        }
        if (lane < 2) {
          stsf(cs + (608 + 4 * lane) * 4, st.m0); stsf(cs + (609 + 4 * lane) * 4, st.l0);
          stsf(cs + (610 + 4 * lane) * 4, st.m1); stsf(cs + (611 + 4 * lane) * 4, st.l1);
        }
      }
      __syncthreads();
      if (WO_AT == 1 && live && lane == 0 && gw < 1024) w_prefetch(wo + opaque(gw) * 4096, 4096);
      const int hq = tid >> 6, dp = tid & 63;
      float mw[8], lw[8], u0[8], u1[8];
#pragma unroll
      for (int w = 0; w < 8; w++) {
        ldsf2(mw[w], lw[w], sb + SM_W0 + (w * CS_WP + 608 + 2 * hq) * 4);
        ldsf2(u0[w], u1[w], sb + SM_W0 + (w * CS_WP + hq * CS_HP + (dp >> 5) * 72 + (dp & 31) * 2) * 4);
      }
      const bool split = head_hi != head_lo;
      float Ma = fmaxf(fmaxf(mw[0], mw[1]), fmaxf(mw[2], mw[3]));
      float Mb = fmaxf(fmaxf(mw[4], mw[5]), fmaxf(mw[6], mw[7]));
      if (!split) Ma = Mb = fmaxf(Ma, Mb);
      float La = 0.f, a0 = 0.f, a1 = 0.f, Lb = 0.f, b0 = 0.f, b1 = 0.f;
#pragma unroll
      for (int w = 0; w < 4; w++) {
        const float ea = ex2(mw[w] - Ma), eb = ex2(mw[w + 4] - Mb);
        La = fmaf(lw[w], ea, La); a0 = fmaf(u0[w], ea, a0); a1 = fmaf(u1[w], ea, a1);
        Lb = fmaf(lw[w + 4], eb, Lb); b0 = fmaf(u0[w + 4], eb, b0); b1 = fmaf(u1[w + 4], eb, b1);
      }
      if (!split) { La += Lb; a0 += b0; a1 += b1; }
      if (live) {
        const int s_lo = cta >> 3;
        const float ia = __fdividef(1.f, La);
        str32(&g_s.PO[ly][head_lo][s_lo][tid], ~pack2(a0 * ia, a1 * ia));
        if (dp == 0) str64(&g_s.ML[ly][head_lo][s_lo][2 * hq], ~__float_as_uint(Ma), ~__float_as_uint(La));
        if (split) {
          const float ib = __fdividef(1.f, Lb);
          str32(&g_s.PO[ly][head_hi][16][tid], ~pack2(b0 * ib, b1 * ib));
          if (dp == 0) str64(&g_s.ML[ly][head_hi][16][2 * hq], ~__float_as_uint(Mb), ~__float_as_uint(Lb));
        }
        TS(31);
        if (tid == 255 && !(sst & 0x2000)) {
          uint32_t target, c;
          asm volatile("ld.shared.u32 %0, [%1];" : "=r"(target) : "r"(sb + SM_STAT + 64) : "memory");
          int it = 0;
          do {
            asm volatile("ld.acquire.gpu.global.u32 %0, [%1];" : "=r"(c) : "l"(&g_s.cnt[ly][0]) : "memory");
            if (++it > SPIN_LIMIT) __trap();
          } while ((int)(c - target) < 0);
        }
      }
      fence_async();
      __syncthreads();
      if (cta < 128) w_issue(&maps.wo, (cta & 15) * 32, (cta >> 4) * 512 + warp * 64, true, true);
    }
    if (live) TS(3 + 10 * layer);
    if (WPF2 && !GU_RANK && live && lane == 0) {
      const int g_ = opaque(gw);
      if (g_ < 448) w_prefetch(wg + g_ * 4096, 4096);
      else if (g_ < 896) w_prefetch(wu + (g_ - 448) * 4096, 4096);
    }

    if (cta < 128) {
      uint32_t A[32];
#pragma unroll
      for (int i = 0; i < 16; i++) A[i] = 0u;
      if (live) {
        {
          const int rb = cta >> 4;
          const uint32_t* pp = pin(&g_s.PO[ly][rb][0][tid]);
          const uint32_t* pm = pin(&g_s.ML[ly][rb][lane < 17 ? lane : 0][2 * (warp >> 1)]);
          uint32_t v[17], um = 0u, ul = 0u;
#pragma unroll
          for (int s = 0; s < 17; s++) v[s] = 0u;
          int it = 0;
          bool pend, done = false;
          do {
            if (um == 0u || ul == 0u) ldr64(um, ul, pm);
#pragma unroll
            for (int s = 0; s < 17; s++)
              if (v[s] == 0u) v[s] = ldr32(pp + s * 256);
            if (!done && __all_sync(0xffffffffu, mbar_test(wbar, 1) && mbar_test(wbar + 8, 1))) {
              w_frags<2>(A, wseg, lane);
              __syncwarp();
              if (cta < 112) w_issue(cta < 56 ? &maps.wg : &maps.wu, (cta < 56 ? cta : cta - 56) * 32, warp * 64, true, false);
              else if (layer == 0) w_issue(&maps.wq, cta * 32, warp * 64, true, false);
              done = true;
              if (layer == 0) TS(27);
            }
            pend = (um == 0u || ul == 0u);
#pragma unroll
            for (int s = 0; s < 17; s++) pend |= (v[s] == 0u);
            if (++it > SPIN_LIMIT) __trap();
          } while (__any_sync(0xffffffffu, pend) || !done);
          TS(4 + 10 * layer);
          const float ms = __uint_as_float(~um);
          int mi = __float_as_int(ms);
          mi = __reduce_max_sync(0xffffffffu, mi ^ ((mi >> 31) & 0x7fffffff));
          const float M = __int_as_float(mi ^ ((mi >> 31) & 0x7fffffff));
          const float e = lane < 17 ? __uint_as_float(~ul) * ex2(ms - M) : 0.f;
          float L = 0.f, o0 = 0.f, o1 = 0.f, Lb = 0.f, p0 = 0.f, p1 = 0.f;
#pragma unroll
          for (int s = 0; s < 17; s++) {
            const float es = __shfl_sync(0xffffffffu, e, s);
            if (s & 1) { Lb += es; p0 = fmaf(es, lo16(~v[s]), p0); p1 = fmaf(es, hi16(~v[s]), p1); }
            else { L += es; o0 = fmaf(es, lo16(~v[s]), o0); o1 = fmaf(es, hi16(~v[s]), o1); }
          }
          o0 += p0; o1 += p1;
          asm volatile("" : "+f"(o0), "+f"(o1));
          w_frags<4, 2>(A, wseg, lane);
          const float inv = __fdividef(1.f, L + Lb);
          const float y = gemv_regs<4, false>(A, sb, warp, lane, pack2(o0 * inv, o1 * inv));
          if (warp == 0) str32(&g_s.Y1[ly][0][0] + cta * 32 + lane, ~__float_as_uint(y));
          if (cta < 112) w_issue(cta < 56 ? &maps.wg : &maps.wu, (cta < 56 ? cta : cta - 56) * 32, warp * 64, false, true);
          else if (layer == 0) w_issue(&maps.wq, cta * 32, warp * 64, false, true);
          __syncthreads();
        }
        TS(5 + 10 * layer);
        if (WPF2 && lane == 0) {
          const int g_ = opaque(gw);
          if (g_ < 448) w_prefetch(wd + g_ * 4096, 4096);
          if (layer == 0) w_prefetch(wq + g_ * 4096, 4096);
        }
#pragma unroll
        for (int i = 0; i < 16; i++) A[i] = 0u;
        xw = add_partials<8>(pin(&g_s.Y1[ly][0][2 * tid]), xw, [&]() {
          if (cta >= 112) return true;
          if (!__all_sync(0xffffffffu, mbar_test(wbar, 0) && mbar_test(wbar + 8, 0))) return false;
          w_frags<2>(A, wseg, lane);
          __syncwarp();
          w_issue(&maps.wd, (cta & 15) * 32, (cta >> 4) * 256 + warp * 32, true, false);
          if (layer == 0) TS(29);
          return true;
        }, [&]() { w_frags<4, 2>(A, wseg, lane); });
        TS(6 + 10 * layer);
        if (cta < 112) {
          const float y = gemv_regs<4, true>(A, sb, warp, lane, xw);
          if (warp == 0) str32(&g_s.GU[ly][cta * 32 + lane], ~__float_as_uint(rbf(y)));
          if (layer == 0) {
            if (lane == 0) mbar_expect(wbar + 8, 0);
            w_issue(&maps.wq, cta * 32, warp * 64, false, true);
          }
          __syncthreads();
          TS(7 + 10 * layer);
#pragma unroll
        for (int i = 0; i < 16; i++) A[i] = 0u;
          const uint32_t* pg = pin(&g_s.GU[ly][(lane >> 4) * FF + (cta >> 4) * 256 + warp * 32 + (lane & 15) * 2]);
          uint32_t a = 0u, b = 0u;
          int it = 0;
          bool done = false;
          do {
            if (a == 0u || b == 0u) ldr64(a, b, pg);
            if (!done && __all_sync(0xffffffffu, mbar_test(wbar, 1))) {
              w_frags<2>(A, wseg, lane);
              __syncwarp();
              if (layer == 0) { w_issue(&maps.wq, cta * 32, warp * 64, true, false); TS(30); }
              done = true;
            }
            if (++it > SPIN_LIMIT) __trap();
          } while (__any_sync(0xffffffffu, a == 0u || b == 0u) || !done);
          TS(8 + 10 * layer);
          const float a0 = __uint_as_float(~a), a1 = __uint_as_float(~b);
          const float c0 = __shfl_xor_sync(0xffffffffu, a0, 16), c1 = __shfl_xor_sync(0xffffffffu, a1, 16);
          const float g0 = lane < 16 ? a0 : c0, g1 = lane < 16 ? a1 : c1;
          const float u0 = lane < 16 ? c0 : a0, u1 = lane < 16 ? c1 : a1;
          const uint32_t hw = pack2((g0 > 0.f ? g0 : g0 * 0.f) * u0, (g1 > 0.f ? g1 : g1 * 0.f) * u1);
          const float y2 = gemv_regs<2, false>(A, sb, warp, lane, hw);
          if (warp == 0) str32(&g_s.Y2[ly][0][0] + cta * 32 + lane, ~__float_as_uint(y2));
          __syncthreads();
          TS(9 + 10 * layer);
        }
        if (layer == 0 && warp == 1) {
          if (lane < 16) g_s.QX[0][cta * 16 + lane] = 0;
          if (lane == 16 && cta < 8) g_s.ctr[0][cta][0] = 0;
        }
        if (layer == 1 && cta != 127) break;
#pragma unroll
        for (int i = 0; i < 16; i++) A[i] = 0u;
        xw = add_partials<7>(pin(&g_s.Y2[ly][0][2 * tid]), xw, [&]() {
          if (layer == 1) return true;
          if (!__all_sync(0xffffffffu, mbar_test(wbar, 0) && mbar_test(wbar + 8, 0))) return false;
          w_frags<2>(A, wseg, lane);
          TS(26);
          return true;
        }, [&]() { w_frags<4, 2>(A, wseg, lane); });
        if (layer == 1) { out[tid] = xw; TS(20); break; }
        TS(10);
        if (KVPF >= 2 && lane == 0) {
          const size_t o_ = (size_t)(head * SK + (T_DYN + jw) * 16) * 256;
          if (KVPF & 1) { l2_prefetch(Kp + o_, 4096); if (KVPF >= 4) l2_prefetch(Vp + o_, 4096); }
          else { ef_prefetch(Kp + o_, 4096); if (KVPF >= 4) ef_prefetch(Vp + o_, 4096); }
        }
      } else {
        mbar_wait(wbar, 0); mbar_wait(wbar + 8, 0);
        w_frags<4>(A, wseg, lane);
        TS(24);
      }
      const float y = gemv_regs<4, true>(A, sb, warp, lane, xw);
      if (warp == 0) {
        const float yh = __shfl_down_sync(0xffffffffu, y, 1);
        if (!(lane & 1)) str32(&g_s.QX[layer + 1][cta * 16 + (lane >> 1)], ~pack2(y, yh));
      }
      if (live) TS(25);
    } else if (layer == 1) {
      break;
    }
    if (!live) {
      const int ln = fresh_lane();
      const uint32_t koff = koff_of(ln), voff = voff_of(ln);
      mbar_wait(rbar + 8, 0);
      if (START2) issue(0, jw + 3 * WPH, false); else issue(2, jw + 2 * WPH, false);
      tile_load_regs(f1, ring + SLOT_BYTES + koff, ring + SLOT_BYTES + voff);
      mbar_wait(rbar + 16, 0);
      if (START2) issue(1, jw + 4 * WPH, false); else issue(0, jw + 3 * WPH, false);
      tile_load_regs(f2, ring + 2 * SLOT_BYTES + koff, ring + 2 * SLOT_BYTES + voff);
    }
    if (KVPF >= 2 && KVPF < 4 && live && lane == 0) {
      const size_t o_ = (size_t)(head * SK + (T_DYN + jw) * 16) * 256;
      if (KVPF & 1) l2_prefetch(Vp + o_, 4096); else ef_prefetch(Vp + o_, 4096);
    }
    __syncthreads();
    {
      const uint32_t* pq = &g_s.QX[layer + 1][head_lo * 256 + tid];
      const int ngrp = head_hi != head_lo ? 2 : 1;
      for (int gi = 0; gi < ngrp; gi++) {
        uint32_t v = 0u;
        int it = 0;
        do {
          if (v == 0u) v = ldr32(pq + gi * 256);
          if (++it > SPIN_LIMIT) __trap();
        } while (__any_sync(0xffffffffu, v == 0u));
        sts32(sb + SM_Q + (gi * 4 + (tid >> 6)) * Q_PITCH + (tid & 63) * 4, ~v);
      }
    }
    __syncthreads();
    TS(layer < 0 ? 1 : 11);
  }
}

typedef CUresult (*EncodeFn)(CUtensorMap*, CUtensorMapDataType, cuuint32_t, void*, const cuuint64_t*,
                             const cuuint64_t*, const cuuint32_t*, const cuuint32_t*, CUtensorMapInterleave,
                             CUtensorMapSwizzle, CUtensorMapL2promotion, CUtensorMapFloatOOBfill);

void make_kv_map(EncodeFn enc, CUtensorMap* m, void* p) {
  cuuint64_t dims[3] = {64, (cuuint64_t)8 * SK, 2};
  cuuint64_t strides[2] = {256, 128};
  cuuint32_t box[3] = {64, 16, 2}, es[3] = {1, 1, 1};
  enc(m, CU_TENSOR_MAP_DATA_TYPE_BFLOAT16, 3, p, dims, strides, box, es, CU_TENSOR_MAP_INTERLEAVE_NONE,
      CU_TENSOR_MAP_SWIZZLE_128B, (CUtensorMapL2promotion)KVPROMO, CU_TENSOR_MAP_FLOAT_OOB_FILL_NONE);
}
void make_w_map(EncodeFn enc, CUtensorMap* m, void* p, int rows, int cols) {
  cuuint64_t dims[2] = {(cuuint64_t)cols, (cuuint64_t)rows};
  cuuint64_t strides[1] = {(cuuint64_t)cols * 2};
  cuuint32_t box[2] = {32, 32}, es[2] = {1, 1};
  enc(m, CU_TENSOR_MAP_DATA_TYPE_BFLOAT16, 2, p, dims, strides, box, es, CU_TENSOR_MAP_INTERLEAVE_NONE,
      CU_TENSOR_MAP_SWIZZLE_64B, CU_TENSOR_MAP_L2_PROMOTION_NONE, CU_TENSOR_MAP_FLOAT_OOB_FILL_NONE);
}

}

extern "C" void kernel_launch(void* const* d_in, const int* in_sizes, int n_in, void* d_out, int out_size) {
  (void)in_sizes; (void)n_in; (void)out_size;
  void* fn = nullptr;
  cudaDriverEntryPointQueryResult qr;
  cudaGetDriverEntryPoint("cuTensorMapEncodeTiled", &fn, cudaEnableDefault, &qr);
  EncodeFn enc = (EncodeFn)fn;
  Maps maps;
  make_kv_map(enc, &maps.k, d_in[1]);
  make_kv_map(enc, &maps.v, d_in[2]);
  make_w_map(enc, &maps.wq, d_in[3], DM, 4096);
  make_w_map(enc, &maps.wo, d_in[4], 4096, DM);
  make_w_map(enc, &maps.wg, d_in[6], DM, FF);
  make_w_map(enc, &maps.wu, d_in[7], DM, FF);
  make_w_map(enc, &maps.wd, d_in[8], FF, DM);
  cudaFuncSetAttribute(decode_kernel, cudaFuncAttributeMaxDynamicSharedMemorySize, SM_TOTAL);
  decode_kernel<<<NCTA, NTHR, SM_TOTAL, cudaStreamPerThread>>>(
      maps, (const uint32_t*)d_in[0], (const char*)d_in[1], (const char*)d_in[2], (const char*)d_in[3],
      (const char*)d_in[4], (const char*)d_in[6], (const char*)d_in[7], (const char*)d_in[8], (uint32_t*)d_out);
}
```

```cpp
#include <cuda_runtime.h>
#include <cuda_bf16.h>
#include <cuda.h>
#include <stdint.h>

namespace {

constexpr int NCTA = 132, NWARP = 8, NTHR = 256;
constexpr int DM = 512, SK = 65536, FF = 1792;
constexpr int WPH = NCTA;
constexpr int SLOT_BYTES = 8192;
#define KEEP_H 760
#define RESET_X 400
#define WPROMO 0
#define NSTAT 7
#define POP_ANY 0
#define SORD 0
#define DEMOTE 3
#define KVPROMO 0
#define DRY 15
#define DRY_L 3
#define DRY_W ((DRY & 1) && ((DRY_L >> layer) & 1))
#define DRY_G ((DRY & 2) && ((DRY_L >> layer) & 1))
#define DRY_D ((DRY & 4) && ((DRY_L >> layer) & 1))
#define DRY_Q ((DRY & 8) && ((DRY_L >> ly) & 1))
#define WO_FIRST 1
#define PF 0
#define SD_W 0
#define SD_G 0
#define SD_D 0
#define SD_S 0
#define WQ_LATE 0
#define W_GATE -1
constexpr int T_DYN = 6 * 132 + 66;
constexpr int T_LAST = 4096 - 132;
constexpr int N_ALL = T_LAST - T_DYN;
constexpr int N_DYN = N_ALL - KEEP_H;
constexpr int KCAP = 12;
static_assert(KCAP * 132 > KEEP_H, "");

constexpr int WARP_BYTES = 28672;
constexpr int O_W = 8192, O_C0 = 12288, O_C1 = 18432, O_E = 24576, O_P = 27648;
constexpr int SM_BAR = NWARP * WARP_BYTES;
constexpr int SM_STAT = SM_BAR + 320;
constexpr int SM_Q = SM_STAT + 128;
constexpr int Q_PITCH = 272;
constexpr int SM_LIST = SM_Q + 2 * 4 * Q_PITCH;
constexpr int SM_ML = SM_LIST + NWARP * KCAP * 2;
constexpr int SM_TOTAL = SM_ML + NWARP * 32;
static_assert(SM_TOTAL <= 232448, "");

struct Scratch {
  uint32_t QX[2][2048];
  uint32_t PO[2][8][17][256];
  uint32_t ML[2][8][17][8];
  uint32_t Y1[2][8][512];
  uint32_t GU[2][2 * FF];
  uint32_t Y2[2][7][512];
  uint32_t cnt[2][32];
  uint32_t ctr[2][8][32];
};
__device__ __align__(1024) Scratch g_s;
#define TS(i) do {} while (0)

struct Maps { CUtensorMap k, v, k2, v2, wq, wo, wg, wu, wd; };

constexpr int SPIN_LIMIT = 1 << 22;

__device__ __forceinline__ void mbar_init(uint32_t bar, int cnt) {
  asm volatile("mbarrier.init.shared::cta.b64 [%0], %1;" ::"r"(bar), "r"(cnt) : "memory");
}
__device__ __forceinline__ void mbar_expect(uint32_t bar, uint32_t bytes) {
  asm volatile("mbarrier.arrive.expect_tx.shared::cta.b64 _, [%0], %1;" ::"r"(bar), "r"(bytes) : "memory");
}
__device__ __forceinline__ void mbar_wait(uint32_t bar, uint32_t parity) {
  uint32_t ok;
  int it = 0;
  do {
    asm volatile("{.reg .pred p; mbarrier.try_wait.parity.shared::cta.b64 p, [%1], %2; selp.u32 %0,1,0,p;}"
                 : "=r"(ok) : "r"(bar), "r"(parity) : "memory");
    if (++it > SPIN_LIMIT) __trap();
  } while (!__all_sync(0xffffffffu, ok));
}
__device__ __forceinline__ bool mbar_test(uint32_t bar, uint32_t parity) {
  uint32_t ok;
  asm volatile("{.reg .pred p; mbarrier.test_wait.parity.shared::cta.b64 p, [%1], %2; selp.u32 %0,1,0,p;}"
               : "=r"(ok) : "r"(bar), "r"(parity) : "memory");
  return ok != 0;
}
__device__ __forceinline__ int fresh_lane() { int l; asm volatile("mov.u32 %0, %laneid;" : "=r"(l)); return l; }
template <class T> __device__ __forceinline__ T* pin(T* p) { asm volatile("" : "+l"(p)); return p; }
__device__ __forceinline__ void delay(uint32_t n) { if (n) { const uint32_t c0 = clock(); while (clock() - c0 < n) {} } }
__device__ __forceinline__ int opaque(int x) { asm volatile("" : "+r"(x)); return x; }
__device__ __forceinline__ void tma3d(uint32_t dst, const CUtensorMap* m, int row, uint32_t bar, uint64_t pol) {
  asm volatile("cp.async.bulk.tensor.3d.shared::cluster.global.mbarrier::complete_tx::bytes.L2::cache_hint"
               " [%0], [%1, {%3, %4, %3}], [%2], %5;"
               ::"r"(dst), "l"(m), "r"(bar), "r"(0), "r"(row), "l"(pol) : "memory");
}
__device__ __forceinline__ void tma2d(uint32_t dst, const CUtensorMap* m, int col, int row, uint32_t bar, uint64_t pol) {
  asm volatile("cp.async.bulk.tensor.2d.shared::cluster.global.mbarrier::complete_tx::bytes.L2::cache_hint"
               " [%0], [%1, {%3, %4}], [%2], %5;"
               ::"r"(dst), "l"(m), "r"(bar), "r"(col), "r"(row), "l"(pol) : "memory");
}
__device__ __forceinline__ void l2_prefetch(const void* p, uint32_t bytes) {
  asm volatile("cp.async.bulk.prefetch.L2.global [%0], %1;" ::"l"(p), "r"(bytes) : "memory");
}
__device__ __forceinline__ uint64_t pol_evict_first() {
  uint64_t p;
  asm volatile("createpolicy.fractional.L2::evict_first.b64 %0, 1.0;" : "=l"(p));
  return p;
}
__device__ __forceinline__ void ldsm4(uint32_t& a, uint32_t& b, uint32_t& c, uint32_t& d, uint32_t addr) {
  asm volatile("ldmatrix.sync.aligned.m8n8.x4.shared.b16 {%0,%1,%2,%3}, [%4];"
               : "=r"(a), "=r"(b), "=r"(c), "=r"(d) : "r"(addr) : "memory");
}
__device__ __forceinline__ void ldsm4t(uint32_t& a, uint32_t& b, uint32_t& c, uint32_t& d, uint32_t addr) {
  asm volatile("ldmatrix.sync.aligned.m8n8.x4.trans.shared.b16 {%0,%1,%2,%3}, [%4];"
               : "=r"(a), "=r"(b), "=r"(c), "=r"(d) : "r"(addr) : "memory");
}
__device__ __forceinline__ void mma(float (&c)[4], uint32_t a0, uint32_t a1, uint32_t a2, uint32_t a3,
                                    uint32_t b0, uint32_t b1) {
  asm volatile("mma.sync.aligned.m16n8k16.row.col.f32.bf16.bf16.f32 {%0,%1,%2,%3}, {%4,%5,%6,%7}, {%8,%9}, {%0,%1,%2,%3};"
               : "+f"(c[0]), "+f"(c[1]), "+f"(c[2]), "+f"(c[3])
               : "r"(a0), "r"(a1), "r"(a2), "r"(a3), "r"(b0), "r"(b1));
}
__device__ __forceinline__ uint32_t movm(uint32_t a) {
  uint32_t d;
  asm volatile("movmatrix.sync.aligned.m8n8.trans.b16 %0, %1;" : "=r"(d) : "r"(a));
  return d;
}
__device__ __forceinline__ uint32_t pack2(float lo, float hi) {
  uint32_t d;
  asm("cvt.rn.bf16x2.f32 %0, %1, %2;" : "=r"(d) : "f"(hi), "f"(lo));
  return d;
}
__device__ __forceinline__ float lo16(uint32_t w) { return __uint_as_float(w << 16); }
__device__ __forceinline__ float hi16(uint32_t w) { return __uint_as_float(w & 0xffff0000u); }
__device__ __forceinline__ float rbf(float x) { return lo16(pack2(x, 0.f)); }
__device__ __forceinline__ float ex2(float x) {
  float y;
  asm("ex2.approx.ftz.f32 %0, %1;" : "=f"(y) : "f"(x));
  return y;
}
__device__ __forceinline__ float rcp(float x) {
  float y;
  asm("rcp.approx.ftz.f32 %0, %1;" : "=f"(y) : "f"(x));
  return y;
}
__device__ __forceinline__ uint32_t enc(uint32_t w) { return w ? w : 0x80000000u; }
__device__ __forceinline__ uint32_t ldr32(const uint32_t* p) {
  uint32_t v;
  asm volatile("ld.relaxed.gpu.global.u32 %0, [%1];" : "=r"(v) : "l"(p) : "memory");
  return v;
}
__device__ __forceinline__ void ldr64(uint32_t& a, uint32_t& b, const uint32_t* p) {
  asm volatile("ld.relaxed.gpu.global.v2.u32 {%0,%1}, [%2];" : "=r"(a), "=r"(b) : "l"(p) : "memory");
}
__device__ __forceinline__ void str32(uint32_t* p, uint32_t v) {
  asm volatile("st.relaxed.gpu.global.u32 [%0], %1;" ::"l"(p), "r"(v) : "memory");
}
__device__ __forceinline__ void str64(uint32_t* p, uint32_t a, uint32_t b) {
  asm volatile("st.relaxed.gpu.global.v2.u32 [%0], {%1,%2};" ::"l"(p), "r"(a), "r"(b) : "memory");
}
__device__ __forceinline__ void sts32(uint32_t addr, uint32_t v) {
  asm volatile("st.shared.u32 [%0], %1;" ::"r"(addr), "r"(v) : "memory");
}
__device__ __forceinline__ void stsf(uint32_t addr, float v) {
  asm volatile("st.shared.f32 [%0], %1;" ::"r"(addr), "f"(v) : "memory");
}
__device__ __forceinline__ void stsf2(uint32_t addr, float a, float b) {
  asm volatile("st.shared.v2.f32 [%0], {%1,%2};" ::"r"(addr), "f"(a), "f"(b) : "memory");
}
__device__ __forceinline__ float ldsf(uint32_t addr) {
  float v;
  asm volatile("ld.shared.f32 %0, [%1];" : "=f"(v) : "r"(addr) : "memory");
  return v;
}
__device__ __forceinline__ void ldsf2(float& a, float& b, uint32_t addr) {
  asm volatile("ld.shared.v2.f32 {%0,%1}, [%2];" : "=f"(a), "=f"(b) : "r"(addr) : "memory");
}
__device__ __forceinline__ void fence_async() { asm volatile("fence.proxy.async.shared::cta;" ::: "memory"); }

constexpr float SCALE_C = 0.08838834764831845f * 1.4426950408889634f;

struct Attn {
  float o[4][4];
  float m0, m1, l0, l1;
};

__device__ __forceinline__ void softmax_step(Attn& st, const float (&s)[4], uint32_t& r0, uint32_t& r1) {
  float t0 = fmaxf(s[0], s[2]), t1 = fmaxf(s[1], s[3]);
#pragma unroll
  for (int o = 4; o <= 16; o <<= 1) {
    t0 = fmaxf(t0, __shfl_xor_sync(0xffffffffu, t0, o));
    t1 = fmaxf(t1, __shfl_xor_sync(0xffffffffu, t1, o));
  }
  float n0 = fmaxf(st.m0, t0 * SCALE_C), n1 = fmaxf(st.m1, t1 * SCALE_C);
  float a0 = ex2(st.m0 - n0), a1 = ex2(st.m1 - n1);
  st.m0 = n0; st.m1 = n1;
  float p0 = ex2(fmaf(s[0], SCALE_C, -n0)), p1 = ex2(fmaf(s[1], SCALE_C, -n1));
  float p2 = ex2(fmaf(s[2], SCALE_C, -n0)), p3 = ex2(fmaf(s[3], SCALE_C, -n1));
  r0 = movm(pack2(p0, p1));
  r1 = movm(pack2(p2, p3));
  st.l0 = fmaf(st.l0, a0, p0 + p2);
  st.l1 = fmaf(st.l1, a1, p1 + p3);
#pragma unroll
  for (int i = 0; i < 4; i++) {
    st.o[i][0] *= a0; st.o[i][1] *= a1; st.o[i][2] *= a0; st.o[i][3] *= a1;
  }
}

__device__ __forceinline__ void tile_smem(Attn& st, uint32_t kaddr, uint32_t vaddr, uint32_t qaddr, bool lowg) {
  float s[4] = {0.f, 0.f, 0.f, 0.f}, s2[4] = {0.f, 0.f, 0.f, 0.f};
#pragma unroll
  for (int j = 0; j < 4; j++) {
    uint32_t q0, q1, q2, q3, a0, a1, a2, a3, c0, c1, c2, c3;
    ldsm4(q0, q1, q2, q3, qaddr + j * 64);
    ldsm4(a0, a1, a2, a3, (kaddr ^ (((2 * j) & 3) << 5)) + (j >> 1) * 2048);
    ldsm4(c0, c1, c2, c3, (kaddr ^ (((2 * j + 1) & 3) << 5)) + (j >> 1) * 2048);
    mma(s, a0, a1, a2, a3, q0, q1);
    mma(s2, c0, c1, c2, c3, q2, q3);
  }
#pragma unroll
  for (int i = 0; i < 4; i++) s[i] += s2[i];
  uint32_t r0, r1;
  softmax_step(st, s, r0, r1);
#pragma unroll
  for (int kg = 0; kg < 2; kg++) {
    uint32_t r = kg ? r1 : r0;
    uint32_t b0 = lowg ? r : 0u, b1 = lowg ? 0u : r;
#pragma unroll
    for (int mt = 0; mt < 4; mt++) {
      uint32_t a0, a1, a2, a3;
      ldsm4t(a0, a1, a2, a3, (vaddr ^ (mt << 5)) + kg * 1024);
      mma(st.o[mt], a0, a1, a2, a3, b0, b1);
    }
  }
}

__device__ __forceinline__ void lds128(uint32_t& a, uint32_t& b, uint32_t& c, uint32_t& d, uint32_t addr) {
  asm volatile("ld.shared.v4.u32 {%0,%1,%2,%3}, [%4];" : "=r"(a), "=r"(b), "=r"(c), "=r"(d) : "r"(addr) : "memory");
}
__device__ __forceinline__ void sts128(uint32_t addr, uint32_t a, uint32_t b, uint32_t c, uint32_t d) {
  asm volatile("st.shared.v4.u32 [%0], {%1,%2,%3,%4};" ::"r"(addr), "r"(a), "r"(b), "r"(c), "r"(d) : "memory");
}

constexpr uint32_t PK_M = 0x78007800u;
constexpr int EXC_CAP = 25;

__device__ __forceinline__ bool pack_prepare(uint32_t img, int lane, int r, uint32_t& bases, uint32_t& exc, uint32_t& cnt) {
  bool ok = true;
  bases = 0;
  uint32_t c = cnt;
#pragma unroll 1
  for (int h = 0; h < 2; h++) {
    const uint32_t base = img + h * 4096 + lane * 16;
    uint32_t mx = 0u, mn = 0x7fff7fffu;
#pragma unroll
    for (int i = 0; i < 8; i++) {
      uint32_t w0, w1, w2, w3;
      lds128(w0, w1, w2, w3, base + i * 512);
      w0 &= 0x7fff7fffu; w1 &= 0x7fff7fffu; w2 &= 0x7fff7fffu; w3 &= 0x7fff7fffu;
      mx = __vimax3_u16x2(mx, w0, w1); mx = __vimax3_u16x2(mx, w2, w3);
      mn = __vimin3_u16x2(mn, w0, w1); mn = __vimin3_u16x2(mn, w2, w3);
    }
    const uint32_t e = __reduce_max_sync(0xffffffffu, max(mx & 0xffffu, mx >> 16)) >> 7;
    const uint32_t B = e > 15u ? e - 15u : 0u, thr = B << 7;
    bases |= B << (8 * h);
    uint32_t todo = __ballot_sync(0xffffffffu, min(mn & 0xffffu, mn >> 16) < thr);
    if (__popc(todo) > 8) ok = false;
    while (todo && ok) {
      const int src = __ffs(todo) - 1;
      todo &= todo - 1;
      const uint32_t off = h * 4096 + src * 16 + (lane >> 2) * 512 + (lane & 3) * 4;
      uint32_t w;
      asm volatile("ld.shared.u32 %0, [%1];" : "=r"(w) : "r"(img + off) : "memory");
#pragma unroll 1
      for (int j = 0; j < 2; j++) {
        const uint32_t v = j ? w >> 16 : w & 0xffffu;
        const bool out = (v & 0x7fffu) < thr;
        uint32_t m = __ballot_sync(0xffffffffu, out);
        if (c + __popc(m) > EXC_CAP) { ok = false; break; }
        if (out) asm volatile("st.shared.u16 [%0], %1;" ::"r"(img + off + 2 * j), "r"(thr) : "memory");
        while (m) {
          const uint32_t en = __shfl_sync(0xffffffffu, (v << 16) | (r << 12) | ((off >> 1) + j), __ffs(m) - 1);
          m &= m - 1;
          if (lane == (int)c) exc = en;
          c++;
        }
      }
    }
  }
  if (ok) cnt = c;
  __syncwarp();
  return ok;
}

__device__ __forceinline__ void pack_tile(uint32_t (&p)[48], uint32_t img, int lane, uint32_t bases) {
  const uint32_t bk = (bases & 0xffu) * 0x00800080u, bv = ((bases >> 8) & 0xffu) * 0x00800080u;
#pragma unroll
  for (int i = 0; i < 16; i++) {
    uint32_t w0, w1, w2, w3;
    lds128(w0, w1, w2, w3, img + lane * 16 + i * 512);
    const uint32_t bb = i < 8 ? bk : bv;
    w3 -= bb;
    p[3 * i] = (w0 - bb) | ((w3 << 11) & PK_M);
    p[3 * i + 1] = (w1 - bb) | ((w3 << 7) & PK_M);
    p[3 * i + 2] = (w2 - bb) | ((w3 << 3) & 0x38003800u) | ((w3 >> 1) & 0x40004000u);
  }
}

__device__ __forceinline__ void unpack_tile(const uint32_t (&p)[48], uint32_t img, int lane, uint32_t bases) {
  const uint32_t bk = (bases & 0xffu) * 0x00800080u, bv = ((bases >> 8) & 0xffu) * 0x00800080u;
#pragma unroll
  for (int i = 0; i < 16; i++) {
    const uint32_t bb = i < 8 ? bk : bv;
    const uint32_t p0 = p[3 * i], p1 = p[3 * i + 1], p2 = p[3 * i + 2];
    const uint32_t w3 = ((p0 >> 11) & 0x000f000fu) | ((p1 >> 7) & 0x00f000f0u) | ((p2 >> 3) & 0x07000700u) | ((p2 << 1) & 0x80008000u);
    sts128(img + lane * 16 + i * 512, (p0 & ~PK_M) + bb, (p1 & ~PK_M) + bb, (p2 & ~PK_M) + bb, w3 + bb);
  }
}

__device__ __forceinline__ uint32_t lds32(uint32_t addr) {
  uint32_t v;
  asm volatile("ld.shared.u32 %0, [%1];" : "=r"(v) : "r"(addr) : "memory");
  return v;
}
__device__ __forceinline__ void pack_tile_smem(uint32_t pk, uint32_t pv, uint32_t img, int lane, uint32_t bases) {
#pragma unroll 1
  for (int h = 0; h < 2; h++) {
    const uint32_t bb = ((bases >> (8 * h)) & 0xffu) * 0x00800080u;
    const uint32_t src = img + h * 4096 + lane * 16, dst = (h ? pv : pk) + lane * 4;
#pragma unroll
    for (int i = 0; i < 8; i++) {
      uint32_t w0, w1, w2, w3;
      lds128(w0, w1, w2, w3, src + i * 512);
      w3 -= bb;
      sts32(dst + i * 384, (w0 - bb) | ((w3 << 11) & PK_M));
      sts32(dst + i * 384 + 128, (w1 - bb) | ((w3 << 7) & PK_M));
      sts32(dst + i * 384 + 256, (w2 - bb) | ((w3 << 3) & 0x38003800u) | ((w3 >> 1) & 0x40004000u));
    }
  }
}
__device__ __forceinline__ void unpack_tile_smem(uint32_t pk, uint32_t pv, uint32_t img, int lane, uint32_t bases) {
#pragma unroll 1
  for (int h = 0; h < 4; h++) {
    const uint32_t bb = ((bases >> (8 * (h >> 1))) & 0xffu) * 0x00800080u;
    const uint32_t dst = img + h * 2048 + lane * 16, src = ((h & 2) ? pv : pk) + (h & 1) * 1536 + lane * 4;
    uint32_t p[12];
#pragma unroll
    for (int i = 0; i < 12; i++) p[i] = lds32(src + i * 128);
    __syncwarp();
#pragma unroll
    for (int i = 0; i < 4; i++) {
      const uint32_t p0 = p[3 * i], p1 = p[3 * i + 1], p2 = p[3 * i + 2];
      const uint32_t w3 = ((p0 >> 11) & 0x000f000fu) | ((p1 >> 7) & 0x00f000f0u) | ((p2 >> 3) & 0x07000700u) | ((p2 << 1) & 0x80008000u);
      sts128(dst + i * 512, (p0 & ~PK_M) + bb, (p1 & ~PK_M) + bb, (p2 & ~PK_M) + bb, w3 + bb);
    }
  }
}

template <int H>
__device__ __forceinline__ void w_frags(uint32_t (&A)[32], uint32_t seg, int lane) {
  const int row = (lane & 7) + ((lane >> 4) << 3);
  const uint32_t base = seg + row * 64 + ((((lane >> 3) & 1) ^ ((row >> 1) & 3)) << 4);
#pragma unroll
  for (int i = 0; i < 4; i++)
    ldsm4t(A[16 * H + 4 * i], A[16 * H + 4 * i + 1], A[16 * H + 4 * i + 2], A[16 * H + 4 * i + 3],
           (base ^ ((i & 1) << 5)) + (i >> 1) * 1024);
}

template <int NKS, bool LN, int FMT>
__device__ __forceinline__ void gemv_regs(const uint32_t (&A)[32], uint32_t sb, int warp, int lane, uint32_t xw,
                                          uint32_t* dst, bool real) {
  float acc[2][4] = {{0.f, 0.f, 0.f, 0.f}, {0.f, 0.f, 0.f, 0.f}};
  const int t = lane & 3, g = lane >> 2;
  float s1 = lo16(xw) + hi16(xw), s2 = fmaf(lo16(xw), lo16(xw), hi16(xw) * hi16(xw));
#pragma unroll
  for (int ks = 0; ks < NKS; ks++) {
    const uint32_t x0 = __shfl_sync(0xffffffffu, xw, 8 * ks + t);
    const uint32_t x1 = __shfl_sync(0xffffffffu, xw, 8 * ks + 4 + t);
    const uint32_t b0 = (LN && (g & 1)) ? 0x3f803f80u : x0, b1 = (LN && (g & 1)) ? 0x3f803f80u : x1;
    mma(acc[0], A[8 * ks], A[8 * ks + 1], A[8 * ks + 2], A[8 * ks + 3], b0, b1);
    mma(acc[1], A[8 * ks + 4], A[8 * ks + 5], A[8 * ks + 6], A[8 * ks + 7], b0, b1);
    if (LN) {
      s1 += __shfl_xor_sync(0xffffffffu, s1, 16 >> ks);
      s2 += __shfl_xor_sync(0xffffffffu, s2, 16 >> ks);
    }
  }
  if (LN) {
    s1 += __shfl_xor_sync(0xffffffffu, s1, 1);
    s2 += __shfl_xor_sync(0xffffffffu, s2, 1);
  }
  const float v = (t & 2) ? ((t & 1) ? acc[1][2] : acc[1][0]) : ((t & 1) ? acc[0][2] : acc[0][0]);
  if (LN) {
    const float cs = (t & 2) ? ((t & 1) ? acc[1][3] : acc[1][1]) : ((t & 1) ? acc[0][3] : acc[0][1]);
    stsf2(sb + SM_Q + (warp * 32 + 8 * t + g) * 8, v, cs);
    if (lane == 0) stsf2(sb + SM_STAT + warp * 8, s2, s1);
  } else {
    stsf(sb + SM_Q + (warp * 32 + 8 * t + g) * 4, v);
  }
  dst = pin(dst);
  uint32_t ra = sb + SM_Q + lane * (LN ? 8 : 4);
  asm volatile("" : "+r"(ra));
  __syncthreads();
  if (warp == 0) {
    float y;
    if (LN) {
      float u[8], c[8], q[8], m[8];
#pragma unroll
      for (int w = 0; w < 8; w++) ldsf2(q[w], m[w], sb + SM_STAT + w * 8);
#pragma unroll
      for (int w = 0; w < 8; w++) ldsf2(u[w], c[w], ra + w * 256);
      const float mean = (((m[0] + m[1]) + (m[2] + m[3])) + ((m[4] + m[5]) + (m[6] + m[7]))) * (1.f / 512.f);
      const float msq = (((q[0] + q[1]) + (q[2] + q[3])) + ((q[4] + q[5]) + (q[6] + q[7]))) * (1.f / 512.f);
      const float vb = rbf(fmaxf(fmaf(-mean, mean, msq), 0.f));
      float sq, rs;
      asm("sqrt.approx.ftz.f32 %0, %1;" : "=f"(sq) : "f"(rbf(vb + 1e-5f)));
      asm("rcp.approx.ftz.f32 %0, %1;" : "=f"(rs) : "f"(rbf(sq)));
      y = ((u[0] + u[1]) + (u[2] + u[3])) + ((u[4] + u[5]) + (u[6] + u[7]));
      const float cs = ((c[0] + c[1]) + (c[2] + c[3])) + ((c[4] + c[5]) + (c[6] + c[7]));
      y = fmaf(-rbf(mean), cs, y) * rs;
    } else {
      float u[8];
#pragma unroll
      for (int w = 0; w < 8; w++) u[w] = ldsf(ra + w * 128);
      y = ((u[0] + u[1]) + (u[2] + u[3])) + ((u[4] + u[5]) + (u[6] + u[7]));
    }
    uint32_t o;
    if (FMT == 2) o = pack2(y, __shfl_down_sync(0xffffffffu, y, 1));
    else o = __float_as_uint(FMT == 1 ? rbf(y) : y);
    o = enc(o);
    asm volatile("{.reg .pred p; setp.ne.u32 p, %2, 0; @p st.relaxed.gpu.global.u32 [%0], %1;}"
                 ::"l"(dst), "r"(o), "r"((uint32_t)(real && (FMT != 2 || !(lane & 1)))) : "memory");
  }
}

template <int NP, class F, class G>
__device__ __forceinline__ uint32_t add_partials(const uint32_t* p, uint32_t xw, bool real, F side, G after) {
  uint32_t a[NP], b[NP];
#pragma unroll
  for (int k = 0; k < NP; k++) a[k] = b[k] = 0u;
  int it = 0;
  bool pend, done = false;
  if (real) do {
#pragma unroll
    for (int k = 0; k < NP; k++)
      if (a[k] == 0u || b[k] == 0u) ldr64(a[k], b[k], p + k * 512);
    if (!done) done = side();
    pend = false;
#pragma unroll
    for (int k = 0; k < NP; k++) pend |= (a[k] == 0u || b[k] == 0u);
    if (!done) done = side();
    if (++it > SPIN_LIMIT) __trap();
  } while (__any_sync(0xffffffffu, pend) || !done);
  float y0 = 0.f, y1 = 0.f;
#pragma unroll
  for (int k = 0; k < NP; k++) { y0 += __uint_as_float(a[k]); y1 += __uint_as_float(b[k]); }
  asm volatile("" : "+f"(y0), "+f"(y1));
  after();
  return pack2(lo16(xw) + rbf(y0), hi16(xw) + rbf(y1));
}

__global__ void __launch_bounds__(NTHR, 1)
decode_kernel(const __grid_constant__ Maps maps, const uint32_t* __restrict__ x_in,
              const char* __restrict__ Kp, const char* __restrict__ Vp, const char* __restrict__ wq,
              const char* __restrict__ wo, const char* __restrict__ wg, const char* __restrict__ wu,
              const char* __restrict__ wd, uint32_t* __restrict__ out) {
  extern __shared__ __align__(1024) unsigned char smem[];
  const uint32_t sb = (uint32_t)__cvta_generic_to_shared(smem);
  const int tid = threadIdx.x, lane = tid & 31;
  const int warp = __shfl_sync(0xffffffffu, tid >> 5, 0);
  const int cta = blockIdx.x;
  const int head_lo = cta < 128 ? (cta & 7) : 2 * (cta - 128), head_hi = cta < 128 ? head_lo : head_lo + 1;
  const int head = warp < 4 ? head_lo : head_hi;
  const int jw = cta < 128 ? (cta >> 3) * 8 + warp : 128 + (warp & 3);
  const uint32_t ring = sb + warp * WARP_BYTES;
  const uint32_t rbar = sb + SM_BAR + warp * 40;
  const uint32_t wbar = rbar + 24;
  const uint32_t wseg = ring + O_W;

  auto w_issue = [&](int half, const CUtensorMap* m, int col, int row) {
    if (lane == 0) {
      mbar_expect(wbar + half * 8, 2048);
      tma2d(wseg + half * 2048, m, col, row, wbar + half * 8, pol_evict_first());
    }
  };
  auto w_pref = [&](const CUtensorMap* m, int col, int row) {
    if (lane == 0)
      asm volatile("cp.async.bulk.prefetch.tensor.2d.L2.global.L2::cache_hint [%0, {%1, %2}], %3;"
                   ::"l"(m), "r"(col), "r"(row), "l"(pol_evict_first()) : "memory");
  };
  auto issue_demote = [&](int sl, int t) {
    if (lane == 0) {
      uint64_t pn;
      asm volatile("createpolicy.fractional.L2::evict_normal.b64 %0, 1.0;" : "=l"(pn));
      const uint64_t pf = pol_evict_first();
      const int row = head * SK + t * 16;
      const uint32_t dst = ring + sl * SLOT_BYTES, b = rbar + sl * 8;
      mbar_expect(b, SLOT_BYTES);
      tma3d(dst, &maps.k, row, b, pn);
      asm volatile("cp.async.bulk.prefetch.L2.global.L2::cache_hint [%0], %1, %2;" ::"l"(Kp + (size_t)row * 256), "r"(4096), "l"(pf) : "memory");
      tma3d(dst + 4096, &maps.v, row, b, pn);
      asm volatile("cp.async.bulk.prefetch.L2.global.L2::cache_hint [%0], %1, %2;" ::"l"(Vp + (size_t)row * 256), "r"(4096), "l"(pf) : "memory");
    }
  };
  auto issue = [&](int sl, int t, bool kp) {
    if (lane == 0) {
      const uint64_t pf = pol_evict_first();
      const int row = head * SK + t * 16;
      const uint32_t dst = ring + sl * SLOT_BYTES, b = rbar + sl * 8;
      mbar_expect(b, SLOT_BYTES);
      tma3d(dst, (kp || !KVPROMO) ? &maps.k : &maps.k2, row, b, pf);
      if (kp) l2_prefetch(Kp + (size_t)row * 256, 4096);
      tma3d(dst + 4096, (kp || !KVPROMO) ? &maps.v : &maps.v2, row, b, pf);
      if (kp) l2_prefetch(Vp + (size_t)row * 256, 4096);
    }
  };
  auto stack_tile = [&](uint32_t r) -> int { return r == 5 ? 6 * WPH + (jw >> 1) : jw + (r == 6 ? 5 : (int)r) * WPH; };

  TS(0);
  uint32_t xw = __ldg(x_in + tid);
  if (lane == 0) {
    if (sb & 1023) __trap();
#pragma unroll
    for (int i = 0; i < 5; i++) mbar_init(rbar + i * 8, 1);
    asm volatile("fence.mbarrier_init.release.cluster;" ::: "memory");
    fence_async();
  }
  if (cta < 128) { w_issue(0, &maps.wq, cta * 32, warp * 64); w_issue(1, &maps.wq, cta * 32, warp * 64 + 32); }
  if (DEMOTE >= 1) issue_demote(2, jw); else issue(2, jw, false);
  if (tid == 32) {
    asm volatile("prefetch.tensormap [%0];" ::"l"(&maps.wo) : "memory");
    asm volatile("prefetch.tensormap [%0];" ::"l"(&maps.wg) : "memory");
    asm volatile("prefetch.tensormap [%0];" ::"l"(&maps.wu) : "memory");
    asm volatile("prefetch.tensormap [%0];" ::"l"(&maps.wd) : "memory");
  }
  __syncwarp();
  TS(21);

  uint32_t c0[48], c1[48], c2[48], c3[48];
#pragma unroll
  for (int i = 0; i < 48; i++) { c0[i] = 0; c1[i] = 0; c2[i] = 0; c3[i] = 0; }
  uint32_t exc = 0;

  uint32_t sst = 0;

  for (int layer = -1; layer < 2; layer++) {
    const bool live = layer >= 0;
    const int ly = live ? layer : 0;

    if (live) {
      Attn st;
#pragma unroll
      for (int i = 0; i < 4; i++) { st.o[i][0] = st.o[i][1] = st.o[i][2] = st.o[i][3] = 0.f; }
      st.m0 = st.m1 = -INFINITY; st.l0 = st.l1 = 0.f;
      const int ln = fresh_lane();
      const uint32_t koff = ((ln & 7) + ((ln >> 3) & 1) * 8) * 128 + (((ln >> 4) ^ (ln & 7)) << 4);
      const uint32_t voff = 4096 + (ln >> 4) * 2048 + (ln & 7) * 128 + ((((ln >> 3) & 1) ^ (ln & 7)) << 4);
      const uint32_t qaddr = sb + SM_Q + ((head - head_lo) * 4 + (ln & 3)) * Q_PITCH + (ln >> 3) * 16;
      const bool lowg = ln < 16;
      int nxt = jw;
      if (layer == 0) { sst = 7; nxt += WPH; }
      else sst = ((sst ^ 0x10) & 0x3ff0770) | 1;
      int spin = 0;
      while (true) {
        int sl = -1;
        if ((sst & 2) && mbar_test(rbar + 8, (sst >> 5) & 1)) sl = 1;
        if (sst & 4) sl = 2;
        if ((sst & 1) && mbar_test(rbar, (sst >> 4) & 1)) sl = 0;
        sl = __shfl_sync(0xffffffffu, sl, 0);
        if (sl >= 0) {
          spin = 0;
          tile_smem(st, ring + sl * SLOT_BYTES + koff, ring + sl * SLOT_BYTES + voff, qaddr, lowg);
          __syncwarp();
          sst ^= 0x11u << sl;
          if (POP_ANY || sl == 0) sst |= 0x2000;
          if (layer == 0) {
            if (sl != 0 || (sst & 0x8000)) {
              const int l_ = fresh_lane();
              const uint32_t r = (sst >> 8) & 7, img = ring + sl * SLOT_BYTES;
              uint32_t bases, cnt = (sst >> 21) & 31;
              if (!pack_prepare(img, l_, r, bases, exc, cnt)) bases |= 0x10000;
              sst = ((sst & ~(31u << 21) & ~0x8000u) | (cnt << 21)) + ((r == 4 && (warp & 1)) ? 0x200 : 0x100);
              if (l_ == EXC_CAP + (int)r) exc = bases;
              if (r == 0) pack_tile(c0, img, l_, bases);
              else if (r == 1) pack_tile(c1, img, l_, bases);
              else if (r == 2) pack_tile(c2, img, l_, bases);
              else if (r == 3) pack_tile(c3, img, l_, bases);
              else {
                const uint32_t pk = ring + (r == 4 ? O_C1 : r == 5 ? O_E : O_C0);
                pack_tile_smem(pk, pk + (r == 5 ? WARP_BYTES : 3072), img, l_, bases);
              }
              fence_async();
              __syncwarp();
              if (sl == 1 && (sst & 0x700) < 0x600) {
                if (DEMOTE >= 4 && ((sst >> 8) & 7) < DEMOTE - 1) issue_demote(1, stack_tile((sst >> 8) & 7));
                else issue(1, stack_tile((sst >> 8) & 7), false);
                sst |= 2;
              }
            }
          } else if (sl == 1 && ((sst >> 16) & 31)) {
            sst -= 1u << 16;
            uint32_t t;
            asm volatile("ld.shared.u16 %0, [%1];" : "=r"(t) : "r"(sb + SM_LIST + warp * (KCAP * 2) + ((sst >> 16) & 31) * 2) : "memory");
            issue(1, t, false); sst |= 2;
          }
        } else if (layer == 1 && (sst & 0x700) && !(sst & 2) && ((sst & 0x2000) || !(sst & 1))) {
          const int l_ = fresh_lane();
          const uint32_t r = ((sst >> 8) & 7) - 1, img = ring + SLOT_BYTES;
          sst = ((sst - ((r == 6 && (warp & 1)) ? 0x200 : 0x100)) | 2) & ~0x2000u;
          const uint32_t hdr = __shfl_sync(0xffffffffu, exc, EXC_CAP + r);
          if (hdr & 0x10000) {
            issue(1, stack_tile(r), false);
          } else {
            if (r == 0) unpack_tile(c0, img, l_, hdr);
            else if (r == 1) unpack_tile(c1, img, l_, hdr);
            else if (r == 2) unpack_tile(c2, img, l_, hdr);
            else if (r == 3) unpack_tile(c3, img, l_, hdr);
            else {
              const uint32_t pk = ring + (r == 4 ? O_C1 : r == 5 ? O_E : O_C0);
              unpack_tile_smem(pk, pk + (r == 5 ? WARP_BYTES : 3072), img, l_, hdr);
            }
            __syncwarp();
            if (l_ < (int)((sst >> 21) & 31) && ((exc >> 12) & 7) == r)
              asm volatile("st.shared.u16 [%0], %1;" ::"r"(img + (exc & 0xfffu) * 2), "r"(exc >> 16) : "memory");
            fence_async();
            __syncwarp();
            if (l_ == 0) mbar_expect(rbar + 8, 0);
          }
          if ((sst & 0x700) == 0) TS(28);
        } else if (warp == 7 && (sst & 0x88) == 8) {
          sst = (sst | 0x80) & ~0x2000u;
          const int l_ = fresh_lane(), c_ = opaque(cta), y_ = opaque(ly);
          const uint4 z = make_uint4(0, 0, 0, 0);
          const int s_lo = c_ >> 3;
          uint4* po = reinterpret_cast<uint4*>(&g_s.PO[y_][head_lo][s_lo][0]);
          po[l_] = z; po[l_ + 32] = z;
          if (l_ < 2) reinterpret_cast<uint4*>(&g_s.ML[y_][head_lo][s_lo][0])[l_] = z;
          if (head_hi != head_lo) {
            po = reinterpret_cast<uint4*>(&g_s.PO[y_][head_hi][16][0]);
            po[l_] = z; po[l_ + 32] = z;
            if (l_ < 2) reinterpret_cast<uint4*>(&g_s.ML[y_][head_hi][16][0])[l_] = z;
          }
          if (c_ < 128) {
            (&g_s.Y1[y_][0][0])[c_ * 32 + l_] = 0;
            if (y_ == 0 && l_ < 16) g_s.QX[1][c_ * 16 + l_] = 0;
          }
          if (c_ < 112) { g_s.GU[y_][c_ * 32 + l_] = 0; (&g_s.Y2[y_][0][0])[c_ * 32 + l_] = 0; }
          if (c_ < 8 && y_ == 0 && l_ == 0) g_s.ctr[1][c_][0] = 0;
          __syncwarp();
          if (l_ == 0) {
            asm volatile("fence.acq_rel.gpu;" ::: "memory");
            const uint32_t old = atomicAdd(&g_s.cnt[y_][0], 1u);
            sts32(sb + SM_STAT + 64, (old / NCTA + 1) * NCTA);
          }
          __syncwarp();
        } else if ((sst & 7) == 0) {
          break;
        } else if ((sst & 0x3080) == 0x2080) {
          uint32_t target, c;
          asm volatile("ld.shared.u32 %0, [%1];" : "=r"(target) : "r"(sb + SM_STAT + 64) : "memory");
          asm volatile("ld.acquire.gpu.global.u32 %0, [%1];" : "=r"(c) : "l"(&g_s.cnt[opaque(ly)][0]) : "memory");
          sst &= ~0x2000u;
          if (__all_sync(0xffffffffu, (int)(c - target) >= 0)) sst |= 0x1000;
        } else if (++spin > SPIN_LIMIT) {
          __trap();
        }
        if (!(sst & 0x801)) {
          if (layer == 0 && (sst & 0x700) == 0x600) {
            issue(0, stack_tile(6), false); sst |= 0x8001;
          } else {
            const int d = __shfl_sync(0xffffffffu, nxt, 8);
            const int nd = layer == 0 ? N_ALL : N_DYN;
            if (d >= nd - RESET_X) sst |= 8;
            if (d < nd) {
              const bool kp = d >= N_DYN;
              issue(0, T_DYN + d, kp); sst |= 1;
              if (kp) {
                if (lane == 0)
                  asm volatile("st.shared.u16 [%0], %1;" ::"r"(sb + SM_LIST + warp * (KCAP * 2) + ((sst >> 16) & 31) * 2), "r"(T_DYN + d) : "memory");
                sst += 1u << 16;
              }
              if (layer == 0 && ((sst >> 16) & 31) == KCAP) nxt = 1 << 20;
              else if (d < (NSTAT - 1) * WPH) nxt = d + WPH;
              else if (lane == 8) nxt = NSTAT * WPH + atomicAdd(&g_s.ctr[layer][head][0], 1u);
            } else if (layer == 1) {
              sst |= 0x800;
            } else if ((sst & 0x700) == 0x700) {
              issue(0, T_LAST + jw, false); sst |= 0x801;
            }
          }
        }
      }
      TS(2 + 10 * layer);
      if (WO_FIRST && cta < 128) {
        w_issue(0, &maps.wo, (cta & 15) * 32, (cta >> 4) * 512 + warp * 64);
        w_issue(1, &maps.wo, (cta & 15) * 32, (cta >> 4) * 512 + warp * 64 + 32);
      }

      {
#pragma unroll
        for (int o = 4; o <= 16; o <<= 1) {
          st.l0 += __shfl_xor_sync(0xffffffffu, st.l0, o);
          st.l1 += __shfl_xor_sync(0xffffffffu, st.l1, o);
        }
        const int g = lane >> 2, t = lane & 3;
        const uint32_t a = ring + O_P + ((t & 1) * 128 + (t >> 1) * 64) * 4;
#pragma unroll
        for (int mt = 0; mt < 4; mt++) {
          sts32(a + ((16 * mt + g) ^ (8 * t)) * 4, pack2(st.o[mt][0], st.o[mt][1]));
          sts32(a + ((16 * mt + 8 + g) ^ (8 * t)) * 4, pack2(st.o[mt][2], st.o[mt][3]));
        }
        if (lane < 2)
          sts128(sb + SM_ML + warp * 32 + lane * 16, __float_as_uint(st.m0), __float_as_uint(st.l0),
                 __float_as_uint(st.m1), __float_as_uint(st.l1));
      }
      {
        const int hp = tid >> 7, d = tid & 127, odd = tid & 1, hq = 2 * hp + odd;
        uint32_t* ppo = pin(&g_s.PO[ly][head_lo][cta >> 3][hq * 64 + (d >> 1)]);
        uint32_t* pml = pin(&g_s.ML[ly][head_lo][cta >> 3][2 * hq]);
        uint32_t am = sb + SM_ML + hp * 16 + odd * 8;
        uint32_t ap = sb + O_P + (hp * 128 + ((d & ~1) ^ (8 * (hp + 2 * (d >> 6))))) * 4;
        uint32_t sel = odd ? 0x7632 : 0x5410;
        asm volatile("" : "+r"(am), "+r"(ap), "+r"(sel));
        if (!WO_FIRST) {
          asm volatile("bar.arrive 1, 512;" ::: "memory");
          if (cta < 128) {
            w_issue(0, &maps.wo, (cta & 15) * 32, (cta >> 4) * 512 + warp * 64);
            w_issue(1, &maps.wo, (cta & 15) * 32, (cta >> 4) * 512 + warp * 64 + 32);
          }
          asm volatile("bar.sync 1, 512;" ::: "memory");
        } else {
          __syncthreads();
        }
        float mw[8], lw[8];
        uint32_t u[8];
#pragma unroll
        for (int w = 0; w < 8; w++) ldsf2(mw[w], lw[w], am + w * 32);
#pragma unroll
        for (int w = 0; w < 8; w++) {
          uint32_t x0, x1;
          asm volatile("ld.shared.v2.u32 {%0,%1}, [%2];" : "=r"(x0), "=r"(x1) : "r"(ap + w * WARP_BYTES) : "memory");
          u[w] = __byte_perm(x0, x1, sel);
        }
        const bool split = head_hi != head_lo;
        float Ma = fmaxf(fmaxf(mw[0], mw[1]), fmaxf(mw[2], mw[3]));
        float Mb = fmaxf(fmaxf(mw[4], mw[5]), fmaxf(mw[6], mw[7]));
        if (!split) Ma = Mb = fmaxf(Ma, Mb);
        float La = 0.f, a0 = 0.f, a1 = 0.f, Lb = 0.f, b0 = 0.f, b1 = 0.f;
#pragma unroll
        for (int w = 0; w < 4; w++) {
          const float ea = ex2(mw[w] - Ma), eb = ex2(mw[w + 4] - Mb);
          La = fmaf(lw[w], ea, La); a0 = fmaf(lo16(u[w]), ea, a0); a1 = fmaf(hi16(u[w]), ea, a1);
          Lb = fmaf(lw[w + 4], eb, Lb); b0 = fmaf(lo16(u[w + 4]), eb, b0); b1 = fmaf(hi16(u[w + 4]), eb, b1);
        }
        if (!split) { La += Lb; a0 += b0; a1 += b1; }
        if (d < 2) str64(pml, enc(__float_as_uint(Ma)), enc(__float_as_uint(La)));
        const float ia = rcp(La);
        str32(ppo, enc(pack2(a0 * ia, a1 * ia)));
        if (split) {
          if (d < 2) str64(pml + 17 * 8, enc(__float_as_uint(Mb)), enc(__float_as_uint(Lb)));
          const float ib = rcp(Lb);
          str32(ppo + 17 * 256, enc(pack2(b0 * ib, b1 * ib)));
        }
      }
      TS(31);
      if (tid == 255 && !(sst & 0x1000)) {
        uint32_t target, c;
        asm volatile("ld.shared.u32 %0, [%1];" : "=r"(target) : "r"(sb + SM_STAT + 64) : "memory");
        int it = 0;
        do {
          asm volatile("ld.acquire.gpu.global.u32 %0, [%1];" : "=r"(c) : "l"(&g_s.cnt[ly][0]) : "memory");
          if (++it > SPIN_LIMIT) __trap();
        } while ((int)(c - target) < 0);
      }
      __syncthreads();
      if ((PF & 1) && cta < 112) w_pref(cta < 56 ? &maps.wg : &maps.wu, (cta < 56 ? cta : cta - 56) * 32, warp * 64 + 32);
      TS(3 + 10 * layer);
    }

    if (cta < 128) {
      uint32_t A[32];
      if (live) {
#pragma unroll 1
        for (int real = DRY_W ? 0 : 1; real < 2; real++) {
#pragma unroll
          for (int i = 0; i < 16; i++) A[i] = 0u;
          const int rb = cta >> 4;
          const uint32_t* pp = pin(&g_s.PO[ly][rb][0][tid]);
          const uint32_t* pm = pin(&g_s.ML[ly][rb][lane < 17 ? lane : 0][2 * (warp >> 1)]);
          uint32_t v[17], um = 0u, ul = 0u;
#pragma unroll
          for (int s = 0; s < 17; s++) v[s] = 0u;
          int it = 0;
          bool pend, done = false;
          const uint32_t tw = clock() + SD_W + warp * SD_S;
          if (real) {
            if (W_GATE >= 0) {
              do {
                if (um == 0u || ul == 0u) ldr64(um, ul, pm);
                if (++it > SPIN_LIMIT) __trap();
              } while (__popc(__ballot_sync(0xffffffffu, (um == 0u || ul == 0u) && lane < 17)) > W_GATE);
            }
            do {
              if (um == 0u || ul == 0u) ldr64(um, ul, pm);
#pragma unroll
              for (int s = 0; s < 17; s++)
                if (v[s] == 0u) v[s] = ldr32(pp + s * 256);
              if (!done && __all_sync(0xffffffffu, (!SD_W || (int)(clock() - tw) >= 0) && mbar_test(wbar, 1))) {
                w_frags<0>(A, wseg, lane);
                __syncwarp();
                if (cta < 112) w_issue(0, cta < 56 ? &maps.wg : &maps.wu, (cta < 56 ? cta : cta - 56) * 32, warp * 64);
                else if (layer == 0) w_issue(0, &maps.wq, cta * 32, warp * 64);
                if ((PF & 2) && cta < 112) w_pref(cta < 56 ? &maps.wg : &maps.wu, (cta < 56 ? cta : cta - 56) * 32, warp * 64 + 32);
                done = true;
                if (layer == 0) TS(27);
              }
              pend = (um == 0u || ul == 0u);
#pragma unroll
              for (int s = 0; s < 17; s++) pend |= (v[s] == 0u);
              if (++it > SPIN_LIMIT) __trap();
            } while (__any_sync(0xffffffffu, pend) || !done);
            TS(4 + 10 * layer);
          }
          const float ms = __uint_as_float(um);
          int mi = __float_as_int(ms);
          mi = __reduce_max_sync(0xffffffffu, mi ^ ((mi >> 31) & 0x7fffffff));
          const float M = __int_as_float(mi ^ ((mi >> 31) & 0x7fffffff));
          const float e = lane < 17 ? __uint_as_float(ul) * ex2(ms - M) : 0.f;
          float L = 0.f, o0 = 0.f, o1 = 0.f, Lb = 0.f, p0 = 0.f, p1 = 0.f;
#pragma unroll
          for (int s = 0; s < 17; s++) {
            const float es = __shfl_sync(0xffffffffu, e, s);
            if (s & 1) { Lb += es; p0 = fmaf(es, lo16(v[s]), p0); p1 = fmaf(es, hi16(v[s]), p1); }
            else { L += es; o0 = fmaf(es, lo16(v[s]), o0); o1 = fmaf(es, hi16(v[s]), o1); }
          }
          o0 += p0; o1 += p1;
          asm volatile("" : "+f"(o0), "+f"(o1));
          if (real) mbar_wait(wbar + 8, 1);
          w_frags<1>(A, wseg + 2048, lane);
          const float inv = rcp(L + Lb);
          gemv_regs<4, false, 0>(A, sb, warp, lane, pack2(o0 * inv, o1 * inv), &g_s.Y1[ly][0][0] + cta * 32 + lane, real);
          if (real) {
            if (cta < 112) w_issue(1, cta < 56 ? &maps.wg : &maps.wu, (cta < 56 ? cta : cta - 56) * 32, warp * 64 + 32);
            else if (layer == 0) w_issue(1, &maps.wq, cta * 32, warp * 64 + 32);
            if ((PF & 4) && cta < 112) w_pref(&maps.wd, (cta & 15) * 32, (cta >> 4) * 256 + warp * 32);
          }
          __syncthreads();
        }
        TS(5 + 10 * layer);
#pragma unroll 1
        for (int real = DRY_G ? 0 : 1; real < 2; real++) {
#pragma unroll
          for (int i = 0; i < 16; i++) A[i] = 0u;
          const uint32_t tw = clock() + SD_G + warp * SD_S;
          const uint32_t xn = add_partials<8>(pin(&g_s.Y1[ly][0][2 * tid]), xw, real, [&]() {
            if (cta >= 112) return true;
            if (!__all_sync(0xffffffffu, (!SD_G || (int)(clock() - tw) >= 0) && mbar_test(wbar, 0))) return false;
            w_frags<0>(A, wseg, lane);
            __syncwarp();
            w_issue(0, &maps.wd, (cta & 15) * 32, (cta >> 4) * 256 + warp * 32);
            if ((PF & 8) && layer == 0) w_pref(&maps.wq, cta * 32, warp * 64 + 32);
            if (layer == 0) TS(29);
            return true;
          }, [&]() { if (real && cta < 112) mbar_wait(wbar + 8, 0); w_frags<1>(A, wseg + 2048, lane); });
          if (real) {
            xw = xn; TS(6 + 10 * layer);
            if ((PF & 16) && layer == 0 && cta < 112) w_pref(&maps.wq, cta * 32, warp * 64 + 32);
            if ((PF & 32) && layer == 0 && cta < 112) w_pref(&maps.wq, cta * 32, warp * 64);
          }
          if (cta < 112) {
            gemv_regs<4, true, 1>(A, sb, warp, lane, xn, &g_s.GU[ly][cta * 32 + lane], real);
            if (real) {
              if (layer == 0) {
                if (lane == 0) mbar_expect(wbar + 8, 0);
                w_issue(1, &maps.wq, cta * 32, warp * 64 + 32);
              }
            }
            __syncthreads();
          }
        }
        if (cta < 112) {
          TS(7 + 10 * layer);
#pragma unroll 1
          for (int real = DRY_D ? 0 : 1; real < 2; real++) {
#pragma unroll
            for (int i = 0; i < 16; i++) A[i] = 0u;
            const uint32_t* pg = pin(&g_s.GU[ly][(lane >> 4) * FF + (cta >> 4) * 256 + warp * 32 + (lane & 15) * 2]);
            uint32_t a = 0u, b = 0u;
            int it = 0;
            bool done = false;
            const uint32_t tw = clock() + (layer == 0 ? SD_D + warp * SD_S : 0);
            if (real) {
              do {
                if (a == 0u || b == 0u) ldr64(a, b, pg);
                if (!done && __all_sync(0xffffffffu, (!SD_D || (int)(clock() - tw) >= 0) && mbar_test(wbar, 1))) {
                  w_frags<0>(A, wseg, lane);
                  __syncwarp();
                  if (layer == 0 && !WQ_LATE) { w_issue(0, &maps.wq, cta * 32, warp * 64); TS(30); }
                  done = true;
                }
                if (++it > SPIN_LIMIT) __trap();
              } while (__any_sync(0xffffffffu, a == 0u || b == 0u) || !done);
              TS(8 + 10 * layer);
            }
            const float a0 = __uint_as_float(a), a1 = __uint_as_float(b);
            const float c0_ = __shfl_xor_sync(0xffffffffu, a0, 16), c1_ = __shfl_xor_sync(0xffffffffu, a1, 16);
            const float g0 = lane < 16 ? a0 : c0_, g1 = lane < 16 ? a1 : c1_;
            const float u0 = lane < 16 ? c0_ : a0, u1 = lane < 16 ? c1_ : a1;
            const uint32_t hw = pack2((g0 > 0.f ? g0 : g0 * 0.f) * u0, (g1 > 0.f ? g1 : g1 * 0.f) * u1);
            if (WQ_LATE == 1 && real && layer == 0) w_issue(0, &maps.wq, cta * 32, warp * 64);
            gemv_regs<2, false, 0>(A, sb, warp, lane, hw, &g_s.Y2[ly][0][0] + cta * 32 + lane, real);
            if (WQ_LATE == 2 && real && layer == 0) w_issue(0, &maps.wq, cta * 32, warp * 64);
            __syncthreads();
          }
          TS(9 + 10 * layer);
        }
        if (layer == 1 && cta != 127) break;
        if (layer == 0 && warp == 4) {
          if (lane < 16) g_s.QX[0][cta * 16 + lane] = 0;
          if (lane == 16 && cta < 8) g_s.ctr[0][cta][0] = 0;
        }
      }
#pragma unroll 1
      for (int real = (DRY_Q && live) ? 0 : 1; real < 2; real++) {
#pragma unroll
        for (int i = 0; i < 16; i++) A[i] = 0u;
        if (!live) {
          mbar_wait(wbar, 0); mbar_wait(wbar + 8, 0);
          w_frags<0>(A, wseg, lane);
          TS(24);
        }
        const uint32_t xn = add_partials<7>(pin(&g_s.Y2[ly][0][2 * tid]), xw, real && live, [&]() {
          if (layer == 1) return true;
          if (!__all_sync(0xffffffffu, mbar_test(wbar, 0) && mbar_test(wbar + 8, 0))) return false;
          w_frags<0>(A, wseg, lane);
          TS(26);
          return true;
        }, [&]() { w_frags<1>(A, wseg + 2048, lane); });
        if (real && live) {
          xw = xn;
          if (layer == 1) { out[tid] = xn; TS(20); return; }
          TS(10);
        }
        gemv_regs<4, true, 2>(A, sb, warp, lane, xw, &g_s.QX[(layer + 1) & 1][cta * 16 + (lane >> 1)], real);
        if (!real) __syncthreads();
      }
      if (live) TS(25);
    } else if (layer == 1) {
      break;
    }
    if (!live) {
      mbar_wait(rbar + 16, 0);
      if (DEMOTE >= 2) issue_demote(1, jw + WPH); else issue(1, jw + WPH, false);
    }
    __syncthreads();
    {
      const uint32_t* pq = &g_s.QX[layer + 1][head_lo * 256 + tid];
      uint32_t qv0 = 0u, qv1 = head_hi != head_lo ? 0u : 1u;
      int it = 0;
      do {
        if (qv0 == 0u) qv0 = ldr32(pq);
        if (qv1 == 0u) qv1 = ldr32(pq + 256);
        if (++it > SPIN_LIMIT) __trap();
      } while (__any_sync(0xffffffffu, qv0 == 0u || qv1 == 0u));
      if (!live) { if (DEMOTE >= 3) issue_demote(0, T_DYN + jw); else issue(0, T_DYN + jw, false); }
      sts32(sb + SM_Q + (tid >> 6) * Q_PITCH + (tid & 63) * 4, qv0);
      sts32(sb + SM_Q + (4 + (tid >> 6)) * Q_PITCH + (tid & 63) * 4, qv1);
    }
    __syncthreads();
    TS(layer < 0 ? 1 : 11);
  }
}

typedef CUresult (*EncodeFn)(CUtensorMap*, CUtensorMapDataType, cuuint32_t, void*, const cuuint64_t*,
                             const cuuint64_t*, const cuuint32_t*, const cuuint32_t*, CUtensorMapInterleave,
                             CUtensorMapSwizzle, CUtensorMapL2promotion, CUtensorMapFloatOOBfill);

void make_kv_map(EncodeFn enc, CUtensorMap* m, void* p, int promo) {
  cuuint64_t dims[3] = {64, (cuuint64_t)8 * SK, 2};
  cuuint64_t strides[2] = {256, 128};
  cuuint32_t box[3] = {64, 16, 2}, es[3] = {1, 1, 1};
  enc(m, CU_TENSOR_MAP_DATA_TYPE_BFLOAT16, 3, p, dims, strides, box, es, CU_TENSOR_MAP_INTERLEAVE_NONE,
      CU_TENSOR_MAP_SWIZZLE_128B, (CUtensorMapL2promotion)promo, CU_TENSOR_MAP_FLOAT_OOB_FILL_NONE);
}
void make_w_map(EncodeFn enc, CUtensorMap* m, void* p, int rows, int cols) {
  cuuint64_t dims[2] = {(cuuint64_t)cols, (cuuint64_t)rows};
  cuuint64_t strides[1] = {(cuuint64_t)cols * 2};
  cuuint32_t box[2] = {32, 32}, es[2] = {1, 1};
  enc(m, CU_TENSOR_MAP_DATA_TYPE_BFLOAT16, 2, p, dims, strides, box, es, CU_TENSOR_MAP_INTERLEAVE_NONE,
      CU_TENSOR_MAP_SWIZZLE_64B, (CUtensorMapL2promotion)WPROMO, CU_TENSOR_MAP_FLOAT_OOB_FILL_NONE);
}

}

extern "C" void kernel_launch(void* const* d_in, const int* in_sizes, int n_in, void* d_out, int out_size) {
  (void)in_sizes; (void)n_in; (void)out_size;
  void* fn = nullptr;
  cudaDriverEntryPointQueryResult qr;
  cudaGetDriverEntryPoint("cuTensorMapEncodeTiled", &fn, cudaEnableDefault, &qr);
  EncodeFn enc = (EncodeFn)fn;
  Maps maps;
  make_kv_map(enc, &maps.k, d_in[1], 0);
  make_kv_map(enc, &maps.v, d_in[2], 0);
  make_kv_map(enc, &maps.k2, d_in[1], KVPROMO);
  make_kv_map(enc, &maps.v2, d_in[2], KVPROMO);
  make_w_map(enc, &maps.wq, d_in[3], DM, 4096);
  make_w_map(enc, &maps.wo, d_in[4], 4096, DM);
  make_w_map(enc, &maps.wg, d_in[6], DM, FF);
  make_w_map(enc, &maps.wu, d_in[7], DM, FF);
  make_w_map(enc, &maps.wd, d_in[8], FF, DM);
  cudaFuncSetAttribute(decode_kernel, cudaFuncAttributeMaxDynamicSharedMemorySize, SM_TOTAL);
  decode_kernel<<<NCTA, NTHR, SM_TOTAL, cudaStreamPerThread>>>(
      maps, (const uint32_t*)d_in[0], (const char*)d_in[1], (const char*)d_in[2], (const char*)d_in[3],
      (const char*)d_in[4], (const char*)d_in[6], (const char*)d_in[7], (const char*)d_in[8], (uint32_t*)d_out);
}
```

```cpp
#include <cuda_runtime.h>
#include <cuda_bf16.h>
#include <cuda.h>
#include <stdint.h>

namespace {

constexpr int NCTA = 132, NWARP = 8, NTHR = 256;
constexpr int DM = 512, SK = 65536, FF = 1792;
constexpr int WPH = NCTA;
constexpr int SLOT_BYTES = 8192;
#define KEEP_H 760
#define RESET_X 400
#define WPROMO 0
#define NSTAT 7
#define POP_ANY 0
#define SORD 0
#define DEMOTE 3
#define KVPROMO 0
#define DRY 15
#define DRY_L 3
#define DRY_W ((DRY & 1) && ((DRY_L >> layer) & 1))
#define DRY_G ((DRY & 2) && ((DRY_L >> layer) & 1))
#define DRY_D ((DRY & 4) && ((DRY_L >> layer) & 1))
#define DRY_Q ((DRY & 8) && ((DRY_L >> ly) & 1))
#define WO_FIRST 1
#define PF 0
#define SD_W 0
#define SD_G 0
#define SD_D 0
#define SD_S 0
#define WQ_LATE 0
#define W_GATE -1
constexpr int T_DYN = 6 * 132 + 66;
constexpr int T_LAST = 4096 - 132;
constexpr int N_ALL = T_LAST - T_DYN;
constexpr int N_DYN = N_ALL - KEEP_H;
constexpr int KCAP = 12;
static_assert(KCAP * 132 > KEEP_H, "");

constexpr int WARP_BYTES = 28672;
constexpr int O_W = 8192, O_C0 = 12288, O_C1 = 18432, O_E = 24576, O_P = 27648;
constexpr int SM_BAR = NWARP * WARP_BYTES;
constexpr int SM_STAT = SM_BAR + 320;
constexpr int SM_Q = SM_STAT + 128;
constexpr int Q_PITCH = 272;
constexpr int SM_LIST = SM_Q + 2 * 4 * Q_PITCH;
constexpr int SM_ML = SM_LIST + NWARP * KCAP * 2;
constexpr int SM_TOTAL = SM_ML + NWARP * 32;
static_assert(SM_TOTAL <= 232448, "");

struct Scratch {
  uint32_t QX[2][2048];
  uint32_t PO[2][8][17][256];
  uint32_t ML[2][8][17][8];
  uint32_t Y1[2][8][512];
  uint32_t GU[2][2 * FF];
  uint32_t Y2[2][7][512];
  uint32_t cnt[2][32];
  uint32_t ctr[2][8][32];
};
__device__ __align__(1024) Scratch g_s;
#define TS(i) do {} while (0)

struct Maps { CUtensorMap k, v, k2, v2, wq, wo, wg, wu, wd; };

constexpr int SPIN_LIMIT = 1 << 22;

__device__ __forceinline__ void mbar_init(uint32_t bar, int cnt) {
  asm volatile("mbarrier.init.shared::cta.b64 [%0], %1;" ::"r"(bar), "r"(cnt) : "memory");
}
__device__ __forceinline__ void mbar_expect(uint32_t bar, uint32_t bytes) {
  asm volatile("mbarrier.arrive.expect_tx.shared::cta.b64 _, [%0], %1;" ::"r"(bar), "r"(bytes) : "memory");
}
__device__ __forceinline__ void mbar_wait(uint32_t bar, uint32_t parity) {
  uint32_t ok;
  int it = 0;
  do {
    asm volatile("{.reg .pred p; mbarrier.try_wait.parity.shared::cta.b64 p, [%1], %2; selp.u32 %0,1,0,p;}"
                 : "=r"(ok) : "r"(bar), "r"(parity) : "memory");
    if (++it > SPIN_LIMIT) __trap();
  } while (!__all_sync(0xffffffffu, ok));
}
__device__ __forceinline__ bool mbar_test(uint32_t bar, uint32_t parity) {
  uint32_t ok;
  asm volatile("{.reg .pred p; mbarrier.test_wait.parity.shared::cta.b64 p, [%1], %2; selp.u32 %0,1,0,p;}"
               : "=r"(ok) : "r"(bar), "r"(parity) : "memory");
  return ok != 0;
}
__device__ __forceinline__ int fresh_lane() { int l; asm volatile("mov.u32 %0, %laneid;" : "=r"(l)); return l; }
template <class T> __device__ __forceinline__ T* pin(T* p) { asm volatile("" : "+l"(p)); return p; }
__device__ __forceinline__ void delay(uint32_t n) { if (n) { const uint32_t c0 = clock(); while (clock() - c0 < n) {} } }
__device__ __forceinline__ int opaque(int x) { asm volatile("" : "+r"(x)); return x; }
__device__ __forceinline__ void tma3d(uint32_t dst, const CUtensorMap* m, int row, uint32_t bar, uint64_t pol) {
  asm volatile("cp.async.bulk.tensor.3d.shared::cluster.global.mbarrier::complete_tx::bytes.L2::cache_hint"
               " [%0], [%1, {%3, %4, %3}], [%2], %5;"
               ::"r"(dst), "l"(m), "r"(bar), "r"(0), "r"(row), "l"(pol) : "memory");
}
__device__ __forceinline__ void tma2d(uint32_t dst, const CUtensorMap* m, int col, int row, uint32_t bar, uint64_t pol) {
  asm volatile("cp.async.bulk.tensor.2d.shared::cluster.global.mbarrier::complete_tx::bytes.L2::cache_hint"
               " [%0], [%1, {%3, %4}], [%2], %5;"
               ::"r"(dst), "l"(m), "r"(bar), "r"(col), "r"(row), "l"(pol) : "memory");
}
__device__ __forceinline__ void l2_prefetch(const void* p, uint32_t bytes) {
  asm volatile("cp.async.bulk.prefetch.L2.global [%0], %1;" ::"l"(p), "r"(bytes) : "memory");
}
__device__ __forceinline__ uint64_t pol_evict_first() {
  uint64_t p;
  asm volatile("createpolicy.fractional.L2::evict_first.b64 %0, 1.0;" : "=l"(p));
  return p;
}
__device__ __forceinline__ void ldsm4(uint32_t& a, uint32_t& b, uint32_t& c, uint32_t& d, uint32_t addr) {
  asm volatile("ldmatrix.sync.aligned.m8n8.x4.shared.b16 {%0,%1,%2,%3}, [%4];"
               : "=r"(a), "=r"(b), "=r"(c), "=r"(d) : "r"(addr) : "memory");
}
__device__ __forceinline__ void ldsm4t(uint32_t& a, uint32_t& b, uint32_t& c, uint32_t& d, uint32_t addr) {
  asm volatile("ldmatrix.sync.aligned.m8n8.x4.trans.shared.b16 {%0,%1,%2,%3}, [%4];"
               : "=r"(a), "=r"(b), "=r"(c), "=r"(d) : "r"(addr) : "memory");
}
__device__ __forceinline__ void mma(float (&c)[4], uint32_t a0, uint32_t a1, uint32_t a2, uint32_t a3,
                                    uint32_t b0, uint32_t b1) {
  asm volatile("mma.sync.aligned.m16n8k16.row.col.f32.bf16.bf16.f32 {%0,%1,%2,%3}, {%4,%5,%6,%7}, {%8,%9}, {%0,%1,%2,%3};"
               : "+f"(c[0]), "+f"(c[1]), "+f"(c[2]), "+f"(c[3])
               : "r"(a0), "r"(a1), "r"(a2), "r"(a3), "r"(b0), "r"(b1));
}
__device__ __forceinline__ uint32_t movm(uint32_t a) {
  uint32_t d;
  asm volatile("movmatrix.sync.aligned.m8n8.trans.b16 %0, %1;" : "=r"(d) : "r"(a));
  return d;
}
__device__ __forceinline__ uint32_t pack2(float lo, float hi) {
  uint32_t d;
  asm("cvt.rn.bf16x2.f32 %0, %1, %2;" : "=r"(d) : "f"(hi), "f"(lo));
  return d;
}
__device__ __forceinline__ float lo16(uint32_t w) { return __uint_as_float(w << 16); }
__device__ __forceinline__ float hi16(uint32_t w) { return __uint_as_float(w & 0xffff0000u); }
__device__ __forceinline__ float rbf(float x) { return lo16(pack2(x, 0.f)); }
__device__ __forceinline__ float ex2(float x) {
  float y;
  asm("ex2.approx.ftz.f32 %0, %1;" : "=f"(y) : "f"(x));
  return y;
}
__device__ __forceinline__ float rcp(float x) {
  float y;
  asm("rcp.approx.ftz.f32 %0, %1;" : "=f"(y) : "f"(x));
  return y;
}
__device__ __forceinline__ uint32_t enc(uint32_t w) { return w ? w : 0x80000000u; }
__device__ __forceinline__ uint32_t ldr32(const uint32_t* p) {
  uint32_t v;
  asm volatile("ld.relaxed.gpu.global.u32 %0, [%1];" : "=r"(v) : "l"(p) : "memory");
  return v;
}
__device__ __forceinline__ void ldr64(uint32_t& a, uint32_t& b, const uint32_t* p) {
  asm volatile("ld.relaxed.gpu.global.v2.u32 {%0,%1}, [%2];" : "=r"(a), "=r"(b) : "l"(p) : "memory");
}
__device__ __forceinline__ void str32(uint32_t* p, uint32_t v) {
  asm volatile("st.relaxed.gpu.global.u32 [%0], %1;" ::"l"(p), "r"(v) : "memory");
}
__device__ __forceinline__ void str64(uint32_t* p, uint32_t a, uint32_t b) {
  asm volatile("st.relaxed.gpu.global.v2.u32 [%0], {%1,%2};" ::"l"(p), "r"(a), "r"(b) : "memory");
}
__device__ __forceinline__ void sts32(uint32_t addr, uint32_t v) {
  asm volatile("st.shared.u32 [%0], %1;" ::"r"(addr), "r"(v) : "memory");
}
__device__ __forceinline__ void stsf(uint32_t addr, float v) {
  asm volatile("st.shared.f32 [%0], %1;" ::"r"(addr), "f"(v) : "memory");
}
__device__ __forceinline__ void stsf2(uint32_t addr, float a, float b) {
  asm volatile("st.shared.v2.f32 [%0], {%1,%2};" ::"r"(addr), "f"(a), "f"(b) : "memory");
}
__device__ __forceinline__ float ldsf(uint32_t addr) {
  float v;
  asm volatile("ld.shared.f32 %0, [%1];" : "=f"(v) : "r"(addr) : "memory");
  return v;
}
__device__ __forceinline__ void ldsf2(float& a, float& b, uint32_t addr) {
  asm volatile("ld.shared.v2.f32 {%0,%1}, [%2];" : "=f"(a), "=f"(b) : "r"(addr) : "memory");
}
__device__ __forceinline__ void fence_async() { asm volatile("fence.proxy.async.shared::cta;" ::: "memory"); }

constexpr float SCALE_C = 0.08838834764831845f * 1.4426950408889634f;

struct Attn {
  float o[4][4];
  float m0, m1, l0, l1;
};

__device__ __forceinline__ void softmax_step(Attn& st, const float (&s)[4], uint32_t& r0, uint32_t& r1) {
  float t0 = fmaxf(s[0], s[2]), t1 = fmaxf(s[1], s[3]);
#pragma unroll
  for (int o = 4; o <= 16; o <<= 1) {
    t0 = fmaxf(t0, __shfl_xor_sync(0xffffffffu, t0, o));
    t1 = fmaxf(t1, __shfl_xor_sync(0xffffffffu, t1, o));
  }
  float n0 = fmaxf(st.m0, t0 * SCALE_C), n1 = fmaxf(st.m1, t1 * SCALE_C);
  float a0 = ex2(st.m0 - n0), a1 = ex2(st.m1 - n1);
  st.m0 = n0; st.m1 = n1;
  float p0 = ex2(fmaf(s[0], SCALE_C, -n0)), p1 = ex2(fmaf(s[1], SCALE_C, -n1));
  float p2 = ex2(fmaf(s[2], SCALE_C, -n0)), p3 = ex2(fmaf(s[3], SCALE_C, -n1));
  r0 = movm(pack2(p0, p1));
  r1 = movm(pack2(p2, p3));
  st.l0 = fmaf(st.l0, a0, p0 + p2);
  st.l1 = fmaf(st.l1, a1, p1 + p3);
#pragma unroll
  for (int i = 0; i < 4; i++) {
    st.o[i][0] *= a0; st.o[i][1] *= a1; st.o[i][2] *= a0; st.o[i][3] *= a1;
  }
}

__device__ __forceinline__ void tile_smem(Attn& st, uint32_t kaddr, uint32_t vaddr, uint32_t qaddr, bool lowg) {
  float s[4] = {0.f, 0.f, 0.f, 0.f}, s2[4] = {0.f, 0.f, 0.f, 0.f};
#pragma unroll
  for (int j = 0; j < 4; j++) {
    uint32_t q0, q1, q2, q3, a0, a1, a2, a3, c0, c1, c2, c3;
    ldsm4(q0, q1, q2, q3, qaddr + j * 64);
    ldsm4(a0, a1, a2, a3, (kaddr ^ (((2 * j) & 3) << 5)) + (j >> 1) * 2048);
    ldsm4(c0, c1, c2, c3, (kaddr ^ (((2 * j + 1) & 3) << 5)) + (j >> 1) * 2048);
    mma(s, a0, a1, a2, a3, q0, q1);
    mma(s2, c0, c1, c2, c3, q2, q3);
  }
#pragma unroll
  for (int i = 0; i < 4; i++) s[i] += s2[i];
  uint32_t r0, r1;
  softmax_step(st, s, r0, r1);
#pragma unroll
  for (int kg = 0; kg < 2; kg++) {
    uint32_t r = kg ? r1 : r0;
    uint32_t b0 = lowg ? r : 0u, b1 = lowg ? 0u : r;
#pragma unroll
    for (int mt = 0; mt < 4; mt++) {
      uint32_t a0, a1, a2, a3;
      ldsm4t(a0, a1, a2, a3, (vaddr ^ (mt << 5)) + kg * 1024);
      mma(st.o[mt], a0, a1, a2, a3, b0, b1);
    }
  }
}

__device__ __forceinline__ void lds128(uint32_t& a, uint32_t& b, uint32_t& c, uint32_t& d, uint32_t addr) {
  asm volatile("ld.shared.v4.u32 {%0,%1,%2,%3}, [%4];" : "=r"(a), "=r"(b), "=r"(c), "=r"(d) : "r"(addr) : "memory");
}
__device__ __forceinline__ void sts128(uint32_t addr, uint32_t a, uint32_t b, uint32_t c, uint32_t d) {
  asm volatile("st.shared.v4.u32 [%0], {%1,%2,%3,%4};" ::"r"(addr), "r"(a), "r"(b), "r"(c), "r"(d) : "memory");
}

constexpr uint32_t PK_M = 0x78007800u, PK_S = 0x80008000u;
constexpr int EXC_CAP = 25;

__device__ __forceinline__ uint32_t lds32(uint32_t addr) {
  uint32_t v;
  asm volatile("ld.shared.u32 %0, [%1];" : "=r"(v) : "r"(addr) : "memory");
  return v;
}

__device__ __forceinline__ bool pack_prepare(uint32_t img, int lane, int r, uint32_t& bases, uint32_t& exc, uint32_t& cnt) {
  bool ok = true;
  bases = 0;
  uint32_t c = cnt;
#pragma unroll 1
  for (int h = 0; h < 2; h++) {
    const uint32_t base = img + h * 4096 + lane * 16;
    uint32_t mx = 0u, mn = 0xffffffffu;
#pragma unroll
    for (int i = 0; i < 8; i++) {
      uint32_t w0, w1, w2, w3;
      lds128(w0, w1, w2, w3, base + i * 512);
      w0 &= ~PK_S; w1 &= ~PK_S; w2 &= ~PK_S; w3 &= ~PK_S;
      mx = __vimax3_u16x2(mx, w0, w1); mx = __vimax3_u16x2(mx, w2, w3);
      mn = __viaddmin_u16x2(w0, 0xffffffffu, mn); mn = __viaddmin_u16x2(w1, 0xffffffffu, mn);
      mn = __viaddmin_u16x2(w2, 0xffffffffu, mn); mn = __viaddmin_u16x2(w3, 0xffffffffu, mn);
    }
    const uint32_t e = __reduce_max_sync(0xffffffffu, max(mx & 0xffffu, mx >> 16)) >> 7;
    const uint32_t B = e > 15u ? e - 15u : 0u, thr = B << 7;
    bases |= B << (8 * h);
    uint32_t todo = __ballot_sync(0xffffffffu, min(mn & 0xffffu, mn >> 16) < thr);
    if (__popc(todo) > 8) ok = false;
    while (todo && ok) {
      const int src = __ffs(todo) - 1;
      todo &= todo - 1;
      const uint32_t off = h * 4096 + src * 16 + (lane >> 2) * 512 + (lane & 3) * 4;
      const uint32_t w = lds32(img + off);
#pragma unroll 1
      for (int j = 0; j < 2; j++) {
        const uint32_t v = j ? w >> 16 : w & 0xffffu;
        uint32_t m = __ballot_sync(0xffffffffu, (v & 0x7fffu) - 1u < thr);
        if (c + __popc(m) > EXC_CAP) { ok = false; break; }
        while (m) {
          const uint32_t en = __shfl_sync(0xffffffffu, (v << 16) | (r << 12) | ((off >> 1) + j), __ffs(m) - 1);
          m &= m - 1;
          if (lane == (int)c) exc = en;
          c++;
        }
      }
    }
  }
  if (ok) cnt = c;
  return ok;
}

__device__ __forceinline__ void pack4(uint32_t& p0, uint32_t& p1, uint32_t& p2, uint32_t w0, uint32_t w1, uint32_t w2,
                                      uint32_t w3, uint32_t nb) {
  const uint32_t x0 = __viaddmax_s16x2(w0 & ~PK_S, nb, 0u), x1 = __viaddmax_s16x2(w1 & ~PK_S, nb, 0u);
  const uint32_t x2 = __viaddmax_s16x2(w2 & ~PK_S, nb, 0u), x3 = __viaddmax_s16x2(w3 & ~PK_S, nb, 0u);
  p0 = x0 | (w0 & PK_S) | ((x3 << 11) & PK_M);
  p1 = x1 | (w1 & PK_S) | ((x3 << 7) & PK_M);
  p2 = x2 | (w2 & PK_S) | ((x3 << 3) & 0x38003800u) | ((w3 >> 1) & 0x40004000u);
}
__device__ __forceinline__ void unpack4_store(uint32_t addr, uint32_t p0, uint32_t p1, uint32_t p2, uint32_t thr) {
  const uint32_t x3 = ((p0 >> 11) & 0x000f000fu) | ((p1 >> 7) & 0x00f000f0u) | ((p2 >> 3) & 0x07000700u);
  sts128(addr, (p0 & ~PK_M) + __vminu2(p0 & 0x07ff07ffu, 0x00010001u) * thr,
         (p1 & ~PK_M) + __vminu2(p1 & 0x07ff07ffu, 0x00010001u) * thr,
         (p2 & ~PK_M) + __vminu2(p2 & 0x07ff07ffu, 0x00010001u) * thr,
         (x3 | ((p2 << 1) & PK_S)) + __vminu2(x3, 0x00010001u) * thr);
}
__device__ __forceinline__ uint32_t neg_base(uint32_t b) { return ((0u - (b << 7)) & 0xffffu) * 0x00010001u; }

__device__ __forceinline__ void pack_tile(uint32_t (&p)[48], uint32_t img, int lane, uint32_t bases) {
  const uint32_t nk = neg_base(bases & 0xffu), nv = neg_base((bases >> 8) & 0xffu);
#pragma unroll
  for (int i = 0; i < 16; i++) {
    uint32_t w0, w1, w2, w3;
    lds128(w0, w1, w2, w3, img + lane * 16 + i * 512);
    pack4(p[3 * i], p[3 * i + 1], p[3 * i + 2], w0, w1, w2, w3, i < 8 ? nk : nv);
  }
}
__device__ __forceinline__ void unpack_tile(const uint32_t (&p)[48], uint32_t img, int lane, uint32_t bases) {
  const uint32_t tk = (bases & 0xffu) << 7, tv = ((bases >> 8) & 0xffu) << 7;
#pragma unroll
  for (int i = 0; i < 16; i++)
    unpack4_store(img + lane * 16 + i * 512, p[3 * i], p[3 * i + 1], p[3 * i + 2], i < 8 ? tk : tv);
}
__device__ __forceinline__ void pack_tile_smem(uint32_t pk, uint32_t pv, uint32_t img, int lane, uint32_t bases) {
#pragma unroll 1
  for (int h = 0; h < 2; h++) {
    const uint32_t nb = neg_base((bases >> (8 * h)) & 0xffu);
    const uint32_t src = img + h * 4096 + lane * 16, dst = (h ? pv : pk) + lane * 4;
#pragma unroll
    for (int i = 0; i < 8; i++) {
      uint32_t w0, w1, w2, w3, p0, p1, p2;
      lds128(w0, w1, w2, w3, src + i * 512);
      pack4(p0, p1, p2, w0, w1, w2, w3, nb);
      sts32(dst + i * 384, p0); sts32(dst + i * 384 + 128, p1); sts32(dst + i * 384 + 256, p2);
    }
  }
}
__device__ __forceinline__ void unpack_tile_smem(uint32_t pk, uint32_t pv, uint32_t img, int lane, uint32_t bases) {
#pragma unroll 1
  for (int h = 0; h < 4; h++) {
    const uint32_t thr = ((bases >> (8 * (h >> 1))) & 0xffu) << 7;
    const uint32_t dst = img + h * 2048 + lane * 16, src = ((h & 2) ? pv : pk) + (h & 1) * 1536 + lane * 4;
    uint32_t p[12];
#pragma unroll
    for (int i = 0; i < 12; i++) p[i] = lds32(src + i * 128);
    __syncwarp();
#pragma unroll
    for (int i = 0; i < 4; i++) unpack4_store(dst + i * 512, p[3 * i], p[3 * i + 1], p[3 * i + 2], thr);
  }
}

template <int H>
__device__ __forceinline__ void w_frags(uint32_t (&A)[32], uint32_t seg, int lane) {
  const int row = (lane & 7) + ((lane >> 4) << 3);
  const uint32_t base = seg + row * 64 + ((((lane >> 3) & 1) ^ ((row >> 1) & 3)) << 4);
#pragma unroll
  for (int i = 0; i < 4; i++)
    ldsm4t(A[16 * H + 4 * i], A[16 * H + 4 * i + 1], A[16 * H + 4 * i + 2], A[16 * H + 4 * i + 3],
           (base ^ ((i & 1) << 5)) + (i >> 1) * 1024);
}

template <int NKS, bool LN, int FMT>
__device__ __forceinline__ void gemv_regs(const uint32_t (&A)[32], uint32_t sb, int warp, int lane, uint32_t xw,
                                          uint32_t* dst, bool real) {
  float acc[2][4] = {{0.f, 0.f, 0.f, 0.f}, {0.f, 0.f, 0.f, 0.f}};
  const int t = lane & 3, g = lane >> 2;
  float s1 = lo16(xw) + hi16(xw), s2 = fmaf(lo16(xw), lo16(xw), hi16(xw) * hi16(xw));
#pragma unroll
  for (int ks = 0; ks < NKS; ks++) {
    const uint32_t x0 = __shfl_sync(0xffffffffu, xw, 8 * ks + t);
    const uint32_t x1 = __shfl_sync(0xffffffffu, xw, 8 * ks + 4 + t);
    const uint32_t b0 = (LN && (g & 1)) ? 0x3f803f80u : x0, b1 = (LN && (g & 1)) ? 0x3f803f80u : x1;
    mma(acc[0], A[8 * ks], A[8 * ks + 1], A[8 * ks + 2], A[8 * ks + 3], b0, b1);
    mma(acc[1], A[8 * ks + 4], A[8 * ks + 5], A[8 * ks + 6], A[8 * ks + 7], b0, b1);
    if (LN) {
      s1 += __shfl_xor_sync(0xffffffffu, s1, 16 >> ks);
      s2 += __shfl_xor_sync(0xffffffffu, s2, 16 >> ks);
    }
  }
  if (LN) {
    s1 += __shfl_xor_sync(0xffffffffu, s1, 1);
    s2 += __shfl_xor_sync(0xffffffffu, s2, 1);
  }
  const float v = (t & 2) ? ((t & 1) ? acc[1][2] : acc[1][0]) : ((t & 1) ? acc[0][2] : acc[0][0]);
  if (LN) {
    const float cs = (t & 2) ? ((t & 1) ? acc[1][3] : acc[1][1]) : ((t & 1) ? acc[0][3] : acc[0][1]);
    stsf2(sb + SM_Q + (warp * 32 + 8 * t + g) * 8, v, cs);
    if (lane == 0) stsf2(sb + SM_STAT + warp * 8, s2, s1);
  } else {
    stsf(sb + SM_Q + (warp * 32 + 8 * t + g) * 4, v);
  }
  dst = pin(dst);
  uint32_t ra = sb + SM_Q + lane * (LN ? 8 : 4);
  asm volatile("" : "+r"(ra));
  __syncthreads();
  if (warp == 0) {
    float y;
    if (LN) {
      float u[8], c[8], q[8], m[8];
#pragma unroll
      for (int w = 0; w < 8; w++) ldsf2(q[w], m[w], sb + SM_STAT + w * 8);
#pragma unroll
      for (int w = 0; w < 8; w++) ldsf2(u[w], c[w], ra + w * 256);
      const float mean = (((m[0] + m[1]) + (m[2] + m[3])) + ((m[4] + m[5]) + (m[6] + m[7]))) * (1.f / 512.f);
      const float msq = (((q[0] + q[1]) + (q[2] + q[3])) + ((q[4] + q[5]) + (q[6] + q[7]))) * (1.f / 512.f);
      const float vb = rbf(fmaxf(fmaf(-mean, mean, msq), 0.f));
      float sq, rs;
      asm("sqrt.approx.ftz.f32 %0, %1;" : "=f"(sq) : "f"(rbf(vb + 1e-5f)));
      asm("rcp.approx.ftz.f32 %0, %1;" : "=f"(rs) : "f"(rbf(sq)));
      y = ((u[0] + u[1]) + (u[2] + u[3])) + ((u[4] + u[5]) + (u[6] + u[7]));
      const float cs = ((c[0] + c[1]) + (c[2] + c[3])) + ((c[4] + c[5]) + (c[6] + c[7]));
      y = fmaf(-rbf(mean), cs, y) * rs;
    } else {
      float u[8];
#pragma unroll
      for (int w = 0; w < 8; w++) u[w] = ldsf(ra + w * 128);
      y = ((u[0] + u[1]) + (u[2] + u[3])) + ((u[4] + u[5]) + (u[6] + u[7]));
    }
    uint32_t o;
    if (FMT == 2) o = pack2(y, __shfl_down_sync(0xffffffffu, y, 1));
    else o = __float_as_uint(FMT == 1 ? rbf(y) : y);
    o = enc(o);
    asm volatile("{.reg .pred p; setp.ne.u32 p, %2, 0; @p st.relaxed.gpu.global.u32 [%0], %1;}"
                 ::"l"(dst), "r"(o), "r"((uint32_t)(real && (FMT != 2 || !(lane & 1)))) : "memory");
  }
}

template <int NP, class F, class G>
__device__ __forceinline__ uint32_t add_partials(const uint32_t* p, uint32_t xw, bool real, F side, G after) {
  uint32_t a[NP], b[NP];
#pragma unroll
  for (int k = 0; k < NP; k++) a[k] = b[k] = 0u;
  int it = 0;
  bool pend, done = false;
  if (real) do {
#pragma unroll
    for (int k = 0; k < NP; k++)
      if (a[k] == 0u || b[k] == 0u) ldr64(a[k], b[k], p + k * 512);
    if (!done) done = side();
    pend = false;
#pragma unroll
    for (int k = 0; k < NP; k++) pend |= (a[k] == 0u || b[k] == 0u);
    if (!done) done = side();
    if (++it > SPIN_LIMIT) __trap();
  } while (__any_sync(0xffffffffu, pend) || !done);
  float y0 = 0.f, y1 = 0.f;
#pragma unroll
  for (int k = 0; k < NP; k++) { y0 += __uint_as_float(a[k]); y1 += __uint_as_float(b[k]); }
  asm volatile("" : "+f"(y0), "+f"(y1));
  after();
  return pack2(lo16(xw) + rbf(y0), hi16(xw) + rbf(y1));
}

__global__ void __launch_bounds__(NTHR, 1)
decode_kernel(const __grid_constant__ Maps maps, const uint32_t* __restrict__ x_in,
              const char* __restrict__ Kp, const char* __restrict__ Vp, const char* __restrict__ wq,
              const char* __restrict__ wo, const char* __restrict__ wg, const char* __restrict__ wu,
              const char* __restrict__ wd, uint32_t* __restrict__ out) {
  extern __shared__ __align__(1024) unsigned char smem[];
  const uint32_t sb = (uint32_t)__cvta_generic_to_shared(smem);
  const int tid = threadIdx.x, lane = tid & 31;
  const int warp = __shfl_sync(0xffffffffu, tid >> 5, 0);
  const int cta = blockIdx.x;
  const int head_lo = cta < 128 ? (cta & 7) : 2 * (cta - 128), head_hi = cta < 128 ? head_lo : head_lo + 1;
  const int head = warp < 4 ? head_lo : head_hi;
  const int jw = cta < 128 ? (cta >> 3) * 8 + warp : 128 + (warp & 3);
  const uint32_t ring = sb + warp * WARP_BYTES;
  const uint32_t rbar = sb + SM_BAR + warp * 40;
  const uint32_t wbar = rbar + 24;
  const uint32_t wseg = ring + O_W;

  auto w_issue = [&](int half, const CUtensorMap* m, int col, int row) {
    if (lane == 0) {
      mbar_expect(wbar + half * 8, 2048);
      tma2d(wseg + half * 2048, m, col, row, wbar + half * 8, pol_evict_first());
    }
  };
  auto w_pref = [&](const CUtensorMap* m, int col, int row) {
    if (lane == 0)
      asm volatile("cp.async.bulk.prefetch.tensor.2d.L2.global.L2::cache_hint [%0, {%1, %2}], %3;"
                   ::"l"(m), "r"(col), "r"(row), "l"(pol_evict_first()) : "memory");
  };
  auto issue_demote = [&](int sl, int t) {
    if (lane == 0) {
      uint64_t pn;
      asm volatile("createpolicy.fractional.L2::evict_normal.b64 %0, 1.0;" : "=l"(pn));
      const uint64_t pf = pol_evict_first();
      const int row = head * SK + t * 16;
      const uint32_t dst = ring + sl * SLOT_BYTES, b = rbar + sl * 8;
      mbar_expect(b, SLOT_BYTES);
      tma3d(dst, &maps.k, row, b, pn);
      asm volatile("cp.async.bulk.prefetch.L2.global.L2::cache_hint [%0], %1, %2;" ::"l"(Kp + (size_t)row * 256), "r"(4096), "l"(pf) : "memory");
      tma3d(dst + 4096, &maps.v, row, b, pn);
      asm volatile("cp.async.bulk.prefetch.L2.global.L2::cache_hint [%0], %1, %2;" ::"l"(Vp + (size_t)row * 256), "r"(4096), "l"(pf) : "memory");
    }
  };
  auto issue = [&](int sl, int t, bool kp) {
    if (lane == 0) {
      const uint64_t pf = pol_evict_first();
      const int row = head * SK + t * 16;
      const uint32_t dst = ring + sl * SLOT_BYTES, b = rbar + sl * 8;
      mbar_expect(b, SLOT_BYTES);
      tma3d(dst, (kp || !KVPROMO) ? &maps.k : &maps.k2, row, b, pf);
      if (kp) l2_prefetch(Kp + (size_t)row * 256, 4096);
      tma3d(dst + 4096, (kp || !KVPROMO) ? &maps.v : &maps.v2, row, b, pf);
      if (kp) l2_prefetch(Vp + (size_t)row * 256, 4096);
    }
  };
  auto stack_tile = [&](uint32_t r) -> int { return r == 5 ? 6 * WPH + (jw >> 1) : jw + (r == 6 ? 5 : (int)r) * WPH; };

  TS(0);
  uint32_t xw = __ldg(x_in + tid);
  if (lane == 0) {
    if (sb & 1023) __trap();
#pragma unroll
    for (int i = 0; i < 5; i++) mbar_init(rbar + i * 8, 1);
    asm volatile("fence.mbarrier_init.release.cluster;" ::: "memory");
    fence_async();
  }
  if (cta < 128) { w_issue(0, &maps.wq, cta * 32, warp * 64); w_issue(1, &maps.wq, cta * 32, warp * 64 + 32); }
  if (DEMOTE >= 1) issue_demote(2, jw); else issue(2, jw, false);
  if (tid == 32) {
    asm volatile("prefetch.tensormap [%0];" ::"l"(&maps.wo) : "memory");
    asm volatile("prefetch.tensormap [%0];" ::"l"(&maps.wg) : "memory");
    asm volatile("prefetch.tensormap [%0];" ::"l"(&maps.wu) : "memory");
    asm volatile("prefetch.tensormap [%0];" ::"l"(&maps.wd) : "memory");
  }
  __syncwarp();
  TS(21);

  uint32_t c0[48], c1[48], c2[48], c3[48];
#pragma unroll
  for (int i = 0; i < 48; i++) { c0[i] = 0; c1[i] = 0; c2[i] = 0; c3[i] = 0; }
  uint32_t exc = 0;

  uint32_t sst = 0;

  for (int layer = -1; layer < 2; layer++) {
    const bool live = layer >= 0;
    const int ly = live ? layer : 0;

    if (live) {
      Attn st;
#pragma unroll
      for (int i = 0; i < 4; i++) { st.o[i][0] = st.o[i][1] = st.o[i][2] = st.o[i][3] = 0.f; }
      st.m0 = st.m1 = -INFINITY; st.l0 = st.l1 = 0.f;
      const int ln = fresh_lane();
      const uint32_t koff = ((ln & 7) + ((ln >> 3) & 1) * 8) * 128 + (((ln >> 4) ^ (ln & 7)) << 4);
      const uint32_t voff = 4096 + (ln >> 4) * 2048 + (ln & 7) * 128 + ((((ln >> 3) & 1) ^ (ln & 7)) << 4);
      const uint32_t qaddr = sb + SM_Q + ((head - head_lo) * 4 + (ln & 3)) * Q_PITCH + (ln >> 3) * 16;
      const bool lowg = ln < 16;
      int nxt = jw;
      if (layer == 0) { sst = 7; nxt += WPH; }
      else sst = ((sst ^ 0x10) & 0x3ff0770) | 1;
      int spin = 0;
      while (true) {
        int sl = -1;
        if ((sst & 2) && mbar_test(rbar + 8, (sst >> 5) & 1)) sl = 1;
        if (sst & 4) sl = 2;
        if ((sst & 1) && mbar_test(rbar, (sst >> 4) & 1)) sl = 0;
        sl = __shfl_sync(0xffffffffu, sl, 0);
        if (sl >= 0) {
          spin = 0;
          tile_smem(st, ring + sl * SLOT_BYTES + koff, ring + sl * SLOT_BYTES + voff, qaddr, lowg);
          __syncwarp();
          sst ^= 0x11u << sl;
          if (POP_ANY || sl == 0) sst |= 0x2000;
          if (layer == 0) {
            if (sl != 0 || (sst & 0x8000)) {
              const int l_ = fresh_lane();
              const uint32_t r = (sst >> 8) & 7, img = ring + sl * SLOT_BYTES;
              uint32_t bases, cnt = (sst >> 21) & 31;
              if (!pack_prepare(img, l_, r, bases, exc, cnt)) bases |= 0x10000;
              sst = ((sst & ~(31u << 21) & ~0x8000u) | (cnt << 21)) + ((r == 4 && (warp & 1)) ? 0x200 : 0x100);
              if (l_ == EXC_CAP + (int)r) exc = bases;
              if (r == 0) pack_tile(c0, img, l_, bases);
              else if (r == 1) pack_tile(c1, img, l_, bases);
              else if (r == 2) pack_tile(c2, img, l_, bases);
              else if (r == 3) pack_tile(c3, img, l_, bases);
              else {
                const uint32_t pk = ring + (r == 4 ? O_C1 : r == 5 ? O_E : O_C0);
                pack_tile_smem(pk, pk + (r == 5 ? WARP_BYTES : 3072), img, l_, bases);
              }
              fence_async();
              __syncwarp();
              if (sl == 1 && (sst & 0x700) < 0x600) {
                if (DEMOTE >= 4 && ((sst >> 8) & 7) < DEMOTE - 1) issue_demote(1, stack_tile((sst >> 8) & 7));
                else issue(1, stack_tile((sst >> 8) & 7), false);
                sst |= 2;
              }
            }
          } else if (sl == 1 && ((sst >> 16) & 31)) {
            sst -= 1u << 16;
            uint32_t t;
            asm volatile("ld.shared.u16 %0, [%1];" : "=r"(t) : "r"(sb + SM_LIST + warp * (KCAP * 2) + ((sst >> 16) & 31) * 2) : "memory");
            issue(1, t, false); sst |= 2;
          }
        } else if (layer == 1 && (sst & 0x700) && !(sst & 2) && ((sst & 0x2000) || !(sst & 1))) {
          const int l_ = fresh_lane();
          const uint32_t r = ((sst >> 8) & 7) - 1, img = ring + SLOT_BYTES;
          sst = ((sst - ((r == 6 && (warp & 1)) ? 0x200 : 0x100)) | 2) & ~0x2000u;
          const uint32_t hdr = __shfl_sync(0xffffffffu, exc, EXC_CAP + r);
          if (hdr & 0x10000) {
            issue(1, stack_tile(r), false);
          } else {
            if (r == 0) unpack_tile(c0, img, l_, hdr);
            else if (r == 1) unpack_tile(c1, img, l_, hdr);
            else if (r == 2) unpack_tile(c2, img, l_, hdr);
            else if (r == 3) unpack_tile(c3, img, l_, hdr);
            else {
              const uint32_t pk = ring + (r == 4 ? O_C1 : r == 5 ? O_E : O_C0);
              unpack_tile_smem(pk, pk + (r == 5 ? WARP_BYTES : 3072), img, l_, hdr);
            }
            __syncwarp();
            if (l_ < (int)((sst >> 21) & 31) && ((exc >> 12) & 7) == r)
              asm volatile("st.shared.u16 [%0], %1;" ::"r"(img + (exc & 0xfffu) * 2), "r"(exc >> 16) : "memory");
            fence_async();
            __syncwarp();
            if (l_ == 0) mbar_expect(rbar + 8, 0);
          }
          if ((sst & 0x700) == 0) TS(28);
        } else if (warp == 7 && (sst & 0x88) == 8) {
          sst = (sst | 0x80) & ~0x2000u;
          const int l_ = fresh_lane(), c_ = opaque(cta), y_ = opaque(ly);
          const uint4 z = make_uint4(0, 0, 0, 0);
          const int s_lo = c_ >> 3;
          uint4* po = reinterpret_cast<uint4*>(&g_s.PO[y_][head_lo][s_lo][0]);
          po[l_] = z; po[l_ + 32] = z;
          if (l_ < 2) reinterpret_cast<uint4*>(&g_s.ML[y_][head_lo][s_lo][0])[l_] = z;
          if (head_hi != head_lo) {
            po = reinterpret_cast<uint4*>(&g_s.PO[y_][head_hi][16][0]);
            po[l_] = z; po[l_ + 32] = z;
            if (l_ < 2) reinterpret_cast<uint4*>(&g_s.ML[y_][head_hi][16][0])[l_] = z;
          }
          if (c_ < 128) {
            (&g_s.Y1[y_][0][0])[c_ * 32 + l_] = 0;
            if (y_ == 0 && l_ < 16) g_s.QX[1][c_ * 16 + l_] = 0;
          }
          if (c_ < 112) { g_s.GU[y_][c_ * 32 + l_] = 0; (&g_s.Y2[y_][0][0])[c_ * 32 + l_] = 0; }
          if (c_ < 8 && y_ == 0 && l_ == 0) g_s.ctr[1][c_][0] = 0;
          __syncwarp();
          if (l_ == 0) {
            asm volatile("fence.acq_rel.gpu;" ::: "memory");
            const uint32_t old = atomicAdd(&g_s.cnt[y_][0], 1u);
            sts32(sb + SM_STAT + 64, (old / NCTA + 1) * NCTA);
          }
          __syncwarp();
        } else if ((sst & 7) == 0) {
          break;
        } else if ((sst & 0x3080) == 0x2080) {
          uint32_t target, c;
          asm volatile("ld.shared.u32 %0, [%1];" : "=r"(target) : "r"(sb + SM_STAT + 64) : "memory");
          asm volatile("ld.acquire.gpu.global.u32 %0, [%1];" : "=r"(c) : "l"(&g_s.cnt[opaque(ly)][0]) : "memory");
          sst &= ~0x2000u;
          if (__all_sync(0xffffffffu, (int)(c - target) >= 0)) sst |= 0x1000;
        } else if (++spin > SPIN_LIMIT) {
          __trap();
        }
        if (!(sst & 0x801)) {
          if (layer == 0 && (sst & 0x700) == 0x600) {
            issue(0, stack_tile(6), false); sst |= 0x8001;
          } else {
            const int d = __shfl_sync(0xffffffffu, nxt, 8);
            const int nd = layer == 0 ? N_ALL : N_DYN;
            if (d >= nd - RESET_X) sst |= 8;
            if (d < nd) {
              const bool kp = d >= N_DYN;
              issue(0, T_DYN + d, kp); sst |= 1;
              if (kp) {
                if (lane == 0)
                  asm volatile("st.shared.u16 [%0], %1;" ::"r"(sb + SM_LIST + warp * (KCAP * 2) + ((sst >> 16) & 31) * 2), "r"(T_DYN + d) : "memory");
                sst += 1u << 16;
              }
              if (layer == 0 && ((sst >> 16) & 31) == KCAP) nxt = 1 << 20;
              else if (d < (NSTAT - 1) * WPH) nxt = d + WPH;
              else if (lane == 8) nxt = NSTAT * WPH + atomicAdd(&g_s.ctr[layer][head][0], 1u);
            } else if (layer == 1) {
              sst |= 0x800;
            } else if ((sst & 0x700) == 0x700) {
              issue(0, T_LAST + jw, false); sst |= 0x801;
            }
          }
        }
      }
      TS(2 + 10 * layer);
      if (WO_FIRST && cta < 128) {
        w_issue(0, &maps.wo, (cta & 15) * 32, (cta >> 4) * 512 + warp * 64);
        w_issue(1, &maps.wo, (cta & 15) * 32, (cta >> 4) * 512 + warp * 64 + 32);
      }

      {
#pragma unroll
        for (int o = 4; o <= 16; o <<= 1) {
          st.l0 += __shfl_xor_sync(0xffffffffu, st.l0, o);
          st.l1 += __shfl_xor_sync(0xffffffffu, st.l1, o);
        }
        const int g = lane >> 2, t = lane & 3;
        const uint32_t a = ring + O_P + ((t & 1) * 128 + (t >> 1) * 64) * 4;
#pragma unroll
        for (int mt = 0; mt < 4; mt++) {
          sts32(a + ((16 * mt + g) ^ (8 * t)) * 4, pack2(st.o[mt][0], st.o[mt][1]));
          sts32(a + ((16 * mt + 8 + g) ^ (8 * t)) * 4, pack2(st.o[mt][2], st.o[mt][3]));
        }
        if (lane < 2)
          sts128(sb + SM_ML + warp * 32 + lane * 16, __float_as_uint(st.m0), __float_as_uint(st.l0),
                 __float_as_uint(st.m1), __float_as_uint(st.l1));
      }
      {
        const int hp = tid >> 7, d = tid & 127, odd = tid & 1, hq = 2 * hp + odd;
        uint32_t* ppo = pin(&g_s.PO[ly][head_lo][cta >> 3][hq * 64 + (d >> 1)]);
        uint32_t* pml = pin(&g_s.ML[ly][head_lo][cta >> 3][2 * hq]);
        uint32_t am = sb + SM_ML + hp * 16 + odd * 8;
        uint32_t ap = sb + O_P + (hp * 128 + ((d & ~1) ^ (8 * (hp + 2 * (d >> 6))))) * 4;
        uint32_t sel = odd ? 0x7632 : 0x5410;
        asm volatile("" : "+r"(am), "+r"(ap), "+r"(sel));
        if (!WO_FIRST) {
          asm volatile("bar.arrive 1, 512;" ::: "memory");
          if (cta < 128) {
            w_issue(0, &maps.wo, (cta & 15) * 32, (cta >> 4) * 512 + warp * 64);
            w_issue(1, &maps.wo, (cta & 15) * 32, (cta >> 4) * 512 + warp * 64 + 32);
          }
          asm volatile("bar.sync 1, 512;" ::: "memory");
        } else {
          __syncthreads();
        }
        float mw[8], lw[8];
        uint32_t u[8];
#pragma unroll
        for (int w = 0; w < 8; w++) ldsf2(mw[w], lw[w], am + w * 32);
#pragma unroll
        for (int w = 0; w < 8; w++) {
          uint32_t x0, x1;
          asm volatile("ld.shared.v2.u32 {%0,%1}, [%2];" : "=r"(x0), "=r"(x1) : "r"(ap + w * WARP_BYTES) : "memory");
          u[w] = __byte_perm(x0, x1, sel);
        }
        const bool split = head_hi != head_lo;
        float Ma = fmaxf(fmaxf(mw[0], mw[1]), fmaxf(mw[2], mw[3]));
        float Mb = fmaxf(fmaxf(mw[4], mw[5]), fmaxf(mw[6], mw[7]));
        if (!split) Ma = Mb = fmaxf(Ma, Mb);
        float La = 0.f, a0 = 0.f, a1 = 0.f, Lb = 0.f, b0 = 0.f, b1 = 0.f;
#pragma unroll
        for (int w = 0; w < 4; w++) {
          const float ea = ex2(mw[w] - Ma), eb = ex2(mw[w + 4] - Mb);
          La = fmaf(lw[w], ea, La); a0 = fmaf(lo16(u[w]), ea, a0); a1 = fmaf(hi16(u[w]), ea, a1);
          Lb = fmaf(lw[w + 4], eb, Lb); b0 = fmaf(lo16(u[w + 4]), eb, b0); b1 = fmaf(hi16(u[w + 4]), eb, b1);
        }
        if (!split) { La += Lb; a0 += b0; a1 += b1; }
        if (d < 2) str64(pml, enc(__float_as_uint(Ma)), enc(__float_as_uint(La)));
        const float ia = rcp(La);
        str32(ppo, enc(pack2(a0 * ia, a1 * ia)));
        if (split) {
          if (d < 2) str64(pml + 17 * 8, enc(__float_as_uint(Mb)), enc(__float_as_uint(Lb)));
          const float ib = rcp(Lb);
          str32(ppo + 17 * 256, enc(pack2(b0 * ib, b1 * ib)));
        }
      }
      TS(31);
      if (tid == 255 && !(sst & 0x1000)) {
        uint32_t target, c;
        asm volatile("ld.shared.u32 %0, [%1];" : "=r"(target) : "r"(sb + SM_STAT + 64) : "memory");
        int it = 0;
        do {
          asm volatile("ld.acquire.gpu.global.u32 %0, [%1];" : "=r"(c) : "l"(&g_s.cnt[ly][0]) : "memory");
          if (++it > SPIN_LIMIT) __trap();
        } while ((int)(c - target) < 0);
      }
      __syncthreads();
      if ((PF & 1) && cta < 112) w_pref(cta < 56 ? &maps.wg : &maps.wu, (cta < 56 ? cta : cta - 56) * 32, warp * 64 + 32);
      TS(3 + 10 * layer);
    }

    if (cta < 128) {
      uint32_t A[32];
      if (live) {
#pragma unroll 1
        for (int real = DRY_W ? 0 : 1; real < 2; real++) {
#pragma unroll
          for (int i = 0; i < 16; i++) A[i] = 0u;
          const int rb = cta >> 4;
          const uint32_t* pp = pin(&g_s.PO[ly][rb][0][tid]);
          const uint32_t* pm = pin(&g_s.ML[ly][rb][lane < 17 ? lane : 0][2 * (warp >> 1)]);
          uint32_t v[17], um = 0u, ul = 0u;
#pragma unroll
          for (int s = 0; s < 17; s++) v[s] = 0u;
          int it = 0;
          bool pend, done = false;
          const uint32_t tw = clock() + SD_W + warp * SD_S;
          if (real) {
            if (W_GATE >= 0) {
              do {
                if (um == 0u || ul == 0u) ldr64(um, ul, pm);
                if (++it > SPIN_LIMIT) __trap();
              } while (__popc(__ballot_sync(0xffffffffu, (um == 0u || ul == 0u) && lane < 17)) > W_GATE);
            }
            do {
              if (um == 0u || ul == 0u) ldr64(um, ul, pm);
#pragma unroll
              for (int s = 0; s < 17; s++)
                if (v[s] == 0u) v[s] = ldr32(pp + s * 256);
              if (!done && __all_sync(0xffffffffu, (!SD_W || (int)(clock() - tw) >= 0) && mbar_test(wbar, 1))) {
                w_frags<0>(A, wseg, lane);
                __syncwarp();
                if (cta < 112) w_issue(0, cta < 56 ? &maps.wg : &maps.wu, (cta < 56 ? cta : cta - 56) * 32, warp * 64);
                else if (layer == 0) w_issue(0, &maps.wq, cta * 32, warp * 64);
                if ((PF & 2) && cta < 112) w_pref(cta < 56 ? &maps.wg : &maps.wu, (cta < 56 ? cta : cta - 56) * 32, warp * 64 + 32);
                done = true;
                if (layer == 0) TS(27);
              }
              pend = (um == 0u || ul == 0u);
#pragma unroll
              for (int s = 0; s < 17; s++) pend |= (v[s] == 0u);
              if (++it > SPIN_LIMIT) __trap();
            } while (__any_sync(0xffffffffu, pend) || !done);
            TS(4 + 10 * layer);
          }
          const float ms = __uint_as_float(um);
          int mi = __float_as_int(ms);
          mi = __reduce_max_sync(0xffffffffu, mi ^ ((mi >> 31) & 0x7fffffff));
          const float M = __int_as_float(mi ^ ((mi >> 31) & 0x7fffffff));
          const float e = lane < 17 ? __uint_as_float(ul) * ex2(ms - M) : 0.f;
          float L = 0.f, o0 = 0.f, o1 = 0.f, Lb = 0.f, p0 = 0.f, p1 = 0.f;
#pragma unroll
          for (int s = 0; s < 17; s++) {
            const float es = __shfl_sync(0xffffffffu, e, s);
            if (s & 1) { Lb += es; p0 = fmaf(es, lo16(v[s]), p0); p1 = fmaf(es, hi16(v[s]), p1); }
            else { L += es; o0 = fmaf(es, lo16(v[s]), o0); o1 = fmaf(es, hi16(v[s]), o1); }
          }
          o0 += p0; o1 += p1;
          asm volatile("" : "+f"(o0), "+f"(o1));
          if (real) mbar_wait(wbar + 8, 1);
          w_frags<1>(A, wseg + 2048, lane);
          const float inv = rcp(L + Lb);
          gemv_regs<4, false, 0>(A, sb, warp, lane, pack2(o0 * inv, o1 * inv), &g_s.Y1[ly][0][0] + cta * 32 + lane, real);
          if (real) {
            if (cta < 112) w_issue(1, cta < 56 ? &maps.wg : &maps.wu, (cta < 56 ? cta : cta - 56) * 32, warp * 64 + 32);
            else if (layer == 0) w_issue(1, &maps.wq, cta * 32, warp * 64 + 32);
            if ((PF & 4) && cta < 112) w_pref(&maps.wd, (cta & 15) * 32, (cta >> 4) * 256 + warp * 32);
          }
          __syncthreads();
        }
        TS(5 + 10 * layer);
#pragma unroll 1
        for (int real = DRY_G ? 0 : 1; real < 2; real++) {
#pragma unroll
          for (int i = 0; i < 16; i++) A[i] = 0u;
          const uint32_t tw = clock() + SD_G + warp * SD_S;
          const uint32_t xn = add_partials<8>(pin(&g_s.Y1[ly][0][2 * tid]), xw, real, [&]() {
            if (cta >= 112) return true;
            if (!__all_sync(0xffffffffu, (!SD_G || (int)(clock() - tw) >= 0) && mbar_test(wbar, 0))) return false;
            w_frags<0>(A, wseg, lane);
            __syncwarp();
            w_issue(0, &maps.wd, (cta & 15) * 32, (cta >> 4) * 256 + warp * 32);
            if ((PF & 8) && layer == 0) w_pref(&maps.wq, cta * 32, warp * 64 + 32);
            if (layer == 0) TS(29);
            return true;
          }, [&]() { if (real && cta < 112) mbar_wait(wbar + 8, 0); w_frags<1>(A, wseg + 2048, lane); });
          if (real) {
            xw = xn; TS(6 + 10 * layer);
            if ((PF & 16) && layer == 0 && cta < 112) w_pref(&maps.wq, cta * 32, warp * 64 + 32);
            if ((PF & 32) && layer == 0 && cta < 112) w_pref(&maps.wq, cta * 32, warp * 64);
          }
          if (cta < 112) {
            gemv_regs<4, true, 1>(A, sb, warp, lane, xn, &g_s.GU[ly][cta * 32 + lane], real);
            if (real) {
              if (layer == 0) {
                if (lane == 0) mbar_expect(wbar + 8, 0);
                w_issue(1, &maps.wq, cta * 32, warp * 64 + 32);
              }
            }
            __syncthreads();
          }
        }
        if (cta < 112) {
          TS(7 + 10 * layer);
#pragma unroll 1
          for (int real = DRY_D ? 0 : 1; real < 2; real++) {
#pragma unroll
            for (int i = 0; i < 16; i++) A[i] = 0u;
            const uint32_t* pg = pin(&g_s.GU[ly][(lane >> 4) * FF + (cta >> 4) * 256 + warp * 32 + (lane & 15) * 2]);
            uint32_t a = 0u, b = 0u;
            int it = 0;
            bool done = false;
            const uint32_t tw = clock() + (layer == 0 ? SD_D + warp * SD_S : 0);
            if (real) {
              do {
                if (a == 0u || b == 0u) ldr64(a, b, pg);
                if (!done && __all_sync(0xffffffffu, (!SD_D || (int)(clock() - tw) >= 0) && mbar_test(wbar, 1))) {
                  w_frags<0>(A, wseg, lane);
                  __syncwarp();
                  if (layer == 0 && !WQ_LATE) { w_issue(0, &maps.wq, cta * 32, warp * 64); TS(30); }
                  done = true;
                }
                if (++it > SPIN_LIMIT) __trap();
              } while (__any_sync(0xffffffffu, a == 0u || b == 0u) || !done);
              TS(8 + 10 * layer);
            }
            const float a0 = __uint_as_float(a), a1 = __uint_as_float(b);
            const float c0_ = __shfl_xor_sync(0xffffffffu, a0, 16), c1_ = __shfl_xor_sync(0xffffffffu, a1, 16);
            const float g0 = lane < 16 ? a0 : c0_, g1 = lane < 16 ? a1 : c1_;
            const float u0 = lane < 16 ? c0_ : a0, u1 = lane < 16 ? c1_ : a1;
            const uint32_t hw = pack2((g0 > 0.f ? g0 : g0 * 0.f) * u0, (g1 > 0.f ? g1 : g1 * 0.f) * u1);
            if (WQ_LATE == 1 && real && layer == 0) w_issue(0, &maps.wq, cta * 32, warp * 64);
            gemv_regs<2, false, 0>(A, sb, warp, lane, hw, &g_s.Y2[ly][0][0] + cta * 32 + lane, real);
            if (WQ_LATE == 2 && real && layer == 0) w_issue(0, &maps.wq, cta * 32, warp * 64);
            __syncthreads();
          }
          TS(9 + 10 * layer);
        }
        if (layer == 1 && cta != 127) break;
        if (layer == 0 && warp == 4) {
          if (lane < 16) g_s.QX[0][cta * 16 + lane] = 0;
          if (lane == 16 && cta < 8) g_s.ctr[0][cta][0] = 0;
        }
      }
#pragma unroll 1
      for (int real = (DRY_Q && live) ? 0 : 1; real < 2; real++) {
#pragma unroll
        for (int i = 0; i < 16; i++) A[i] = 0u;
        if (!live) {
          mbar_wait(wbar, 0); mbar_wait(wbar + 8, 0);
          w_frags<0>(A, wseg, lane);
          TS(24);
        }
        const uint32_t xn = add_partials<7>(pin(&g_s.Y2[ly][0][2 * tid]), xw, real && live, [&]() {
          if (layer == 1) return true;
          if (!__all_sync(0xffffffffu, mbar_test(wbar, 0) && mbar_test(wbar + 8, 0))) return false;
          w_frags<0>(A, wseg, lane);
          TS(26);
          return true;
        }, [&]() { w_frags<1>(A, wseg + 2048, lane); });
        if (real && live) {
          xw = xn;
          if (layer == 1) { out[tid] = xn; TS(20); return; }
          TS(10);
        }
        gemv_regs<4, true, 2>(A, sb, warp, lane, xw, &g_s.QX[(layer + 1) & 1][cta * 16 + (lane >> 1)], real);
        if (!real) __syncthreads();
      }
      if (live) TS(25);
    } else if (layer == 1) {
      break;
    }
    if (!live) {
      mbar_wait(rbar + 16, 0);
      if (DEMOTE >= 2) issue_demote(1, jw + WPH); else issue(1, jw + WPH, false);
    }
    __syncthreads();
    {
      const uint32_t* pq = &g_s.QX[layer + 1][head_lo * 256 + tid];
      uint32_t qv0 = 0u, qv1 = head_hi != head_lo ? 0u : 1u;
      int it = 0;
      do {
        if (qv0 == 0u) qv0 = ldr32(pq);
        if (qv1 == 0u) qv1 = ldr32(pq + 256);
        if (++it > SPIN_LIMIT) __trap();
      } while (__any_sync(0xffffffffu, qv0 == 0u || qv1 == 0u));
      if (!live) { if (DEMOTE >= 3) issue_demote(0, T_DYN + jw); else issue(0, T_DYN + jw, false); }
      sts32(sb + SM_Q + (tid >> 6) * Q_PITCH + (tid & 63) * 4, qv0);
      sts32(sb + SM_Q + (4 + (tid >> 6)) * Q_PITCH + (tid & 63) * 4, qv1);
    }
    __syncthreads();
    TS(layer < 0 ? 1 : 11);
  }
}

typedef CUresult (*EncodeFn)(CUtensorMap*, CUtensorMapDataType, cuuint32_t, void*, const cuuint64_t*,
                             const cuuint64_t*, const cuuint32_t*, const cuuint32_t*, CUtensorMapInterleave,
                             CUtensorMapSwizzle, CUtensorMapL2promotion, CUtensorMapFloatOOBfill);

void make_kv_map(EncodeFn enc, CUtensorMap* m, void* p, int promo) {
  cuuint64_t dims[3] = {64, (cuuint64_t)8 * SK, 2};
  cuuint64_t strides[2] = {256, 128};
  cuuint32_t box[3] = {64, 16, 2}, es[3] = {1, 1, 1};
  enc(m, CU_TENSOR_MAP_DATA_TYPE_BFLOAT16, 3, p, dims, strides, box, es, CU_TENSOR_MAP_INTERLEAVE_NONE,
      CU_TENSOR_MAP_SWIZZLE_128B, (CUtensorMapL2promotion)promo, CU_TENSOR_MAP_FLOAT_OOB_FILL_NONE);
}
void make_w_map(EncodeFn enc, CUtensorMap* m, void* p, int rows, int cols) {
  cuuint64_t dims[2] = {(cuuint64_t)cols, (cuuint64_t)rows};
  cuuint64_t strides[1] = {(cuuint64_t)cols * 2};
  cuuint32_t box[2] = {32, 32}, es[2] = {1, 1};
  enc(m, CU_TENSOR_MAP_DATA_TYPE_BFLOAT16, 2, p, dims, strides, box, es, CU_TENSOR_MAP_INTERLEAVE_NONE,
      CU_TENSOR_MAP_SWIZZLE_64B, (CUtensorMapL2promotion)WPROMO, CU_TENSOR_MAP_FLOAT_OOB_FILL_NONE);
}

}

extern "C" void kernel_launch(void* const* d_in, const int* in_sizes, int n_in, void* d_out, int out_size) {
  (void)in_sizes; (void)n_in; (void)out_size;
  void* fn = nullptr;
  cudaDriverEntryPointQueryResult qr;
  cudaGetDriverEntryPoint("cuTensorMapEncodeTiled", &fn, cudaEnableDefault, &qr);
  EncodeFn enc = (EncodeFn)fn;
  Maps maps;
  make_kv_map(enc, &maps.k, d_in[1], 0);
  make_kv_map(enc, &maps.v, d_in[2], 0);
  make_kv_map(enc, &maps.k2, d_in[1], KVPROMO);
  make_kv_map(enc, &maps.v2, d_in[2], KVPROMO);
  make_w_map(enc, &maps.wq, d_in[3], DM, 4096);
  make_w_map(enc, &maps.wo, d_in[4], 4096, DM);
  make_w_map(enc, &maps.wg, d_in[6], DM, FF);
  make_w_map(enc, &maps.wu, d_in[7], DM, FF);
  make_w_map(enc, &maps.wd, d_in[8], FF, DM);
  cudaFuncSetAttribute(decode_kernel, cudaFuncAttributeMaxDynamicSharedMemorySize, SM_TOTAL);
  decode_kernel<<<NCTA, NTHR, SM_TOTAL, cudaStreamPerThread>>>(
      maps, (const uint32_t*)d_in[0], (const char*)d_in[1], (const char*)d_in[2], (const char*)d_in[3],
      (const char*)d_in[4], (const char*)d_in[6], (const char*)d_in[7], (const char*)d_in[8], (uint32_t*)d_out);
}
```

```cpp
#include <cuda_runtime.h>
#include <cuda_bf16.h>
#include <cuda.h>
#include <stdint.h>

namespace {

constexpr int NCTA = 132, NWARP = 8, NTHR = 256;
constexpr int DM = 512, SK = 65536, FF = 1792;
constexpr int WPH = NCTA;
constexpr int SLOT_BYTES = 8192;
#define KEEP_H 760
#define RESET_X 400
#define WO_K 25
#define WO_R0 60
#define STOP_M 0x11
#define STOP_X0 700
#define STOP_X1 700
#define STOP_R -80
#define NSTAT 4
constexpr int T_DYN = 6 * 132 + 66;
constexpr int T_LAST = 4096 - 132;
constexpr int N_ALL = T_LAST - T_DYN;
constexpr int N_DYN = N_ALL - KEEP_H;
constexpr int KCAP = 12;
static_assert(STOP_M == 0x11 && KCAP * 99 > KEEP_H, "the warps that stream to the end must be able to take all kept tiles");
static_assert(N_DYN - STOP_X1 >= NSTAT * 132 && N_ALL - STOP_X0 >= NSTAT * 132, "");

constexpr int WARP_BYTES = 28672;
constexpr int O_W = 8192, O_C0 = 12288, O_C1 = 18432, O_E = 24576, O_P = 27648;
constexpr int SM_BAR = NWARP * WARP_BYTES;
constexpr int SM_STAT = SM_BAR + 320;
constexpr int SM_Q = SM_STAT + 128;
constexpr int Q_PITCH = 272;
constexpr int SM_LIST = SM_Q + 2 * 4 * Q_PITCH;
constexpr int SM_ML = SM_LIST + NWARP * KCAP * 2;
constexpr int SM_TOTAL = SM_ML + NWARP * 32;
static_assert(SM_TOTAL <= 232448, "");

struct Scratch {
  uint32_t QX[2][2048];
  uint32_t PO[2][8][17][256];
  uint32_t ML[2][8][17][8];
  uint32_t Y1[2][8][512];
  uint32_t GU[2][2 * FF];
  uint32_t Y2[2][7][512];
  uint32_t cnt[2][32];
  uint32_t ctr[2][8][32];
};
__device__ __align__(1024) Scratch g_s;
#define TS(i) do {} while (0)

struct Maps { CUtensorMap k, v, wq, wo, wg, wu, wd; };

constexpr int SPIN_LIMIT = 1 << 22;

__device__ __forceinline__ void mbar_init(uint32_t bar, int cnt) {
  asm volatile("mbarrier.init.shared::cta.b64 [%0], %1;" ::"r"(bar), "r"(cnt) : "memory");
}
__device__ __forceinline__ void mbar_expect(uint32_t bar, uint32_t bytes) {
  asm volatile("mbarrier.arrive.expect_tx.shared::cta.b64 _, [%0], %1;" ::"r"(bar), "r"(bytes) : "memory");
}
__device__ __forceinline__ void mbar_wait(uint32_t bar, uint32_t parity) {
  uint32_t ok;
  int it = 0;
  do {
    asm volatile("{.reg .pred p; mbarrier.try_wait.parity.shared::cta.b64 p, [%1], %2; selp.u32 %0,1,0,p;}"
                 : "=r"(ok) : "r"(bar), "r"(parity) : "memory");
    if (++it > SPIN_LIMIT) __trap();
  } while (!__all_sync(0xffffffffu, ok));
}
__device__ __forceinline__ bool mbar_test(uint32_t bar, uint32_t parity) {
  uint32_t ok;
  asm volatile("{.reg .pred p; mbarrier.test_wait.parity.shared::cta.b64 p, [%1], %2; selp.u32 %0,1,0,p;}"
               : "=r"(ok) : "r"(bar), "r"(parity) : "memory");
  return ok != 0;
}
__device__ __forceinline__ int fresh_lane() { int l; asm volatile("mov.u32 %0, %laneid;" : "=r"(l)); return l; }
template <class T> __device__ __forceinline__ T* pin(T* p) { asm volatile("" : "+l"(p)); return p; }
__device__ __forceinline__ int opaque(int x) { asm volatile("" : "+r"(x)); return x; }
__device__ __forceinline__ void tma3d(uint32_t dst, const CUtensorMap* m, int row, uint32_t bar, uint64_t pol) {
  asm volatile("cp.async.bulk.tensor.3d.shared::cluster.global.mbarrier::complete_tx::bytes.L2::cache_hint"
               " [%0], [%1, {%3, %4, %3}], [%2], %5;"
               ::"r"(dst), "l"(m), "r"(bar), "r"(0), "r"(row), "l"(pol) : "memory");
}
__device__ __forceinline__ void tma2d(uint32_t dst, const CUtensorMap* m, int col, int row, uint32_t bar, uint64_t pol) {
  asm volatile("cp.async.bulk.tensor.2d.shared::cluster.global.mbarrier::complete_tx::bytes.L2::cache_hint"
               " [%0], [%1, {%3, %4}], [%2], %5;"
               ::"r"(dst), "l"(m), "r"(bar), "r"(col), "r"(row), "l"(pol) : "memory");
}
__device__ __forceinline__ void l2_prefetch(const void* p, uint32_t bytes) {
  asm volatile("cp.async.bulk.prefetch.L2.global [%0], %1;" ::"l"(p), "r"(bytes) : "memory");
}
__device__ __forceinline__ uint64_t pol_evict_first() {
  uint64_t p;
  asm volatile("createpolicy.fractional.L2::evict_first.b64 %0, 1.0;" : "=l"(p));
  return p;
}
__device__ __forceinline__ void ldsm4(uint32_t& a, uint32_t& b, uint32_t& c, uint32_t& d, uint32_t addr) {
  asm volatile("ldmatrix.sync.aligned.m8n8.x4.shared.b16 {%0,%1,%2,%3}, [%4];"
               : "=r"(a), "=r"(b), "=r"(c), "=r"(d) : "r"(addr) : "memory");
}
__device__ __forceinline__ void ldsm4t(uint32_t& a, uint32_t& b, uint32_t& c, uint32_t& d, uint32_t addr) {
  asm volatile("ldmatrix.sync.aligned.m8n8.x4.trans.shared.b16 {%0,%1,%2,%3}, [%4];"
               : "=r"(a), "=r"(b), "=r"(c), "=r"(d) : "r"(addr) : "memory");
}
__device__ __forceinline__ void mma(float (&c)[4], uint32_t a0, uint32_t a1, uint32_t a2, uint32_t a3,
                                    uint32_t b0, uint32_t b1) {
  asm volatile("mma.sync.aligned.m16n8k16.row.col.f32.bf16.bf16.f32 {%0,%1,%2,%3}, {%4,%5,%6,%7}, {%8,%9}, {%0,%1,%2,%3};"
               : "+f"(c[0]), "+f"(c[1]), "+f"(c[2]), "+f"(c[3])
               : "r"(a0), "r"(a1), "r"(a2), "r"(a3), "r"(b0), "r"(b1));
}
__device__ __forceinline__ uint32_t movm(uint32_t a) {
  uint32_t d;
  asm volatile("movmatrix.sync.aligned.m8n8.trans.b16 %0, %1;" : "=r"(d) : "r"(a));
  return d;
}
__device__ __forceinline__ uint32_t pack2(float lo, float hi) {
  uint32_t d;
  asm("cvt.rn.bf16x2.f32 %0, %1, %2;" : "=r"(d) : "f"(hi), "f"(lo));
  return d;
}
__device__ __forceinline__ float lo16(uint32_t w) { return __uint_as_float(w << 16); }
__device__ __forceinline__ float hi16(uint32_t w) { return __uint_as_float(w & 0xffff0000u); }
__device__ __forceinline__ float rbf(float x) { return lo16(pack2(x, 0.f)); }
__device__ __forceinline__ float ex2(float x) {
  float y;
  asm("ex2.approx.ftz.f32 %0, %1;" : "=f"(y) : "f"(x));
  return y;
}
__device__ __forceinline__ float rcp(float x) {
  float y;
  asm("rcp.approx.ftz.f32 %0, %1;" : "=f"(y) : "f"(x));
  return y;
}
__device__ __forceinline__ uint32_t enc(uint32_t w) { return w ? w : 0x80000000u; }
__device__ __forceinline__ uint32_t ldr32(const uint32_t* p) {
  uint32_t v;
  asm volatile("ld.relaxed.gpu.global.u32 %0, [%1];" : "=r"(v) : "l"(p) : "memory");
  return v;
}
__device__ __forceinline__ void ldr64(uint32_t& a, uint32_t& b, const uint32_t* p) {
  asm volatile("ld.relaxed.gpu.global.v2.u32 {%0,%1}, [%2];" : "=r"(a), "=r"(b) : "l"(p) : "memory");
}
__device__ __forceinline__ void str32(uint32_t* p, uint32_t v) {
  asm volatile("st.relaxed.gpu.global.u32 [%0], %1;" ::"l"(p), "r"(v) : "memory");
}
__device__ __forceinline__ void str64(uint32_t* p, uint32_t a, uint32_t b) {
  asm volatile("st.relaxed.gpu.global.v2.u32 [%0], {%1,%2};" ::"l"(p), "r"(a), "r"(b) : "memory");
}
__device__ __forceinline__ void sts32(uint32_t addr, uint32_t v) {
  asm volatile("st.shared.u32 [%0], %1;" ::"r"(addr), "r"(v) : "memory");
}
__device__ __forceinline__ void stsf(uint32_t addr, float v) {
  asm volatile("st.shared.f32 [%0], %1;" ::"r"(addr), "f"(v) : "memory");
}
__device__ __forceinline__ void stsf2(uint32_t addr, float a, float b) {
  asm volatile("st.shared.v2.f32 [%0], {%1,%2};" ::"r"(addr), "f"(a), "f"(b) : "memory");
}
__device__ __forceinline__ float ldsf(uint32_t addr) {
  float v;
  asm volatile("ld.shared.f32 %0, [%1];" : "=f"(v) : "r"(addr) : "memory");
  return v;
}
__device__ __forceinline__ void ldsf2(float& a, float& b, uint32_t addr) {
  asm volatile("ld.shared.v2.f32 {%0,%1}, [%2];" : "=f"(a), "=f"(b) : "r"(addr) : "memory");
}
__device__ __forceinline__ void fence_async() { asm volatile("fence.proxy.async.shared::cta;" ::: "memory"); }

constexpr float SCALE_C = 0.08838834764831845f * 1.4426950408889634f;

struct Attn {
  float o[4][4];
  float m0, m1, l0, l1;
};

__device__ __forceinline__ void softmax_step(Attn& st, const float (&s)[4], uint32_t& r0, uint32_t& r1) {
  float t0 = fmaxf(s[0], s[2]), t1 = fmaxf(s[1], s[3]);
#pragma unroll
  for (int o = 4; o <= 16; o <<= 1) {
    t0 = fmaxf(t0, __shfl_xor_sync(0xffffffffu, t0, o));
    t1 = fmaxf(t1, __shfl_xor_sync(0xffffffffu, t1, o));
  }
  float n0 = fmaxf(st.m0, t0 * SCALE_C), n1 = fmaxf(st.m1, t1 * SCALE_C);
  float a0 = ex2(st.m0 - n0), a1 = ex2(st.m1 - n1);
  st.m0 = n0; st.m1 = n1;
  float p0 = ex2(fmaf(s[0], SCALE_C, -n0)), p1 = ex2(fmaf(s[1], SCALE_C, -n1));
  float p2 = ex2(fmaf(s[2], SCALE_C, -n0)), p3 = ex2(fmaf(s[3], SCALE_C, -n1));
  r0 = movm(pack2(p0, p1));
  r1 = movm(pack2(p2, p3));
  st.l0 = fmaf(st.l0, a0, p0 + p2);
  st.l1 = fmaf(st.l1, a1, p1 + p3);
#pragma unroll
  for (int i = 0; i < 4; i++) {
    st.o[i][0] *= a0; st.o[i][1] *= a1; st.o[i][2] *= a0; st.o[i][3] *= a1;
  }
}

__device__ __forceinline__ void tile_smem(Attn& st, uint32_t kaddr, uint32_t vaddr, uint32_t qaddr, bool lowg) {
  float s[4] = {0.f, 0.f, 0.f, 0.f}, s2[4] = {0.f, 0.f, 0.f, 0.f};
#pragma unroll
  for (int j = 0; j < 4; j++) {
    uint32_t q0, q1, q2, q3, a0, a1, a2, a3, c0, c1, c2, c3;
    ldsm4(q0, q1, q2, q3, qaddr + j * 64);
    ldsm4(a0, a1, a2, a3, (kaddr ^ (((2 * j) & 3) << 5)) + (j >> 1) * 2048);
    ldsm4(c0, c1, c2, c3, (kaddr ^ (((2 * j + 1) & 3) << 5)) + (j >> 1) * 2048);
    mma(s, a0, a1, a2, a3, q0, q1);
    mma(s2, c0, c1, c2, c3, q2, q3);
  }
#pragma unroll
  for (int i = 0; i < 4; i++) s[i] += s2[i];
  uint32_t r0, r1;
  softmax_step(st, s, r0, r1);
#pragma unroll
  for (int kg = 0; kg < 2; kg++) {
    uint32_t r = kg ? r1 : r0;
    uint32_t b0 = lowg ? r : 0u, b1 = lowg ? 0u : r;
#pragma unroll
    for (int mt = 0; mt < 4; mt++) {
      uint32_t a0, a1, a2, a3;
      ldsm4t(a0, a1, a2, a3, (vaddr ^ (mt << 5)) + kg * 1024);
      mma(st.o[mt], a0, a1, a2, a3, b0, b1);
    }
  }
}

__device__ __forceinline__ void lds128(uint32_t& a, uint32_t& b, uint32_t& c, uint32_t& d, uint32_t addr) {
  asm volatile("ld.shared.v4.u32 {%0,%1,%2,%3}, [%4];" : "=r"(a), "=r"(b), "=r"(c), "=r"(d) : "r"(addr) : "memory");
}
__device__ __forceinline__ void sts128(uint32_t addr, uint32_t a, uint32_t b, uint32_t c, uint32_t d) {
  asm volatile("st.shared.v4.u32 [%0], {%1,%2,%3,%4};" ::"r"(addr), "r"(a), "r"(b), "r"(c), "r"(d) : "memory");
}

constexpr uint32_t PK_M = 0x78007800u, PK_S = 0x80008000u;
constexpr int EXC_CAP = 25;

__device__ __forceinline__ uint32_t lds32(uint32_t addr) {
  uint32_t v;
  asm volatile("ld.shared.u32 %0, [%1];" : "=r"(v) : "r"(addr) : "memory");
  return v;
}

__device__ __forceinline__ bool pack_prepare(uint32_t img, int lane, int r, uint32_t& bases, uint32_t& exc, uint32_t& cnt) {
  bool ok = true;
  bases = 0;
  uint32_t c = cnt;
#pragma unroll 1
  for (int h = 0; h < 2; h++) {
    const uint32_t base = img + h * 4096 + lane * 16;
    uint32_t mx = 0u, mn = 0xffffffffu;
#pragma unroll
    for (int i = 0; i < 8; i++) {
      uint32_t w0, w1, w2, w3;
      lds128(w0, w1, w2, w3, base + i * 512);
      w0 &= ~PK_S; w1 &= ~PK_S; w2 &= ~PK_S; w3 &= ~PK_S;
      mx = __vimax3_u16x2(mx, w0, w1); mx = __vimax3_u16x2(mx, w2, w3);
      mn = __viaddmin_u16x2(w0, 0xffffffffu, mn); mn = __viaddmin_u16x2(w1, 0xffffffffu, mn);
      mn = __viaddmin_u16x2(w2, 0xffffffffu, mn); mn = __viaddmin_u16x2(w3, 0xffffffffu, mn);
    }
    const uint32_t e = __reduce_max_sync(0xffffffffu, max(mx & 0xffffu, mx >> 16)) >> 7;
    const uint32_t B = e > 15u ? e - 15u : 0u, thr = B << 7;
    bases |= B << (8 * h);
    uint32_t todo = __ballot_sync(0xffffffffu, min(mn & 0xffffu, mn >> 16) < thr);
    if (__popc(todo) > 8) ok = false;
    while (todo && ok) {
      const int src = __ffs(todo) - 1;
      todo &= todo - 1;
      const uint32_t off = h * 4096 + src * 16 + (lane >> 2) * 512 + (lane & 3) * 4;
      const uint32_t w = lds32(img + off);
#pragma unroll 1
      for (int j = 0; j < 2; j++) {
        const uint32_t v = j ? w >> 16 : w & 0xffffu;
        uint32_t m = __ballot_sync(0xffffffffu, (v & 0x7fffu) - 1u < thr);
        if (c + __popc(m) > EXC_CAP) { ok = false; break; }
        while (m) {
          const uint32_t en = __shfl_sync(0xffffffffu, (v << 16) | (r << 12) | ((off >> 1) + j), __ffs(m) - 1);
          m &= m - 1;
          if (lane == (int)c) exc = en;
          c++;
        }
      }
    }
  }
  if (ok) cnt = c;
  return ok;
}

__device__ __forceinline__ void pack4(uint32_t& p0, uint32_t& p1, uint32_t& p2, uint32_t w0, uint32_t w1, uint32_t w2,
                                      uint32_t w3, uint32_t nb) {
  const uint32_t x0 = __viaddmax_s16x2(w0 & ~PK_S, nb, 0u), x1 = __viaddmax_s16x2(w1 & ~PK_S, nb, 0u);
  const uint32_t x2 = __viaddmax_s16x2(w2 & ~PK_S, nb, 0u), x3 = __viaddmax_s16x2(w3 & ~PK_S, nb, 0u);
  p0 = x0 | (w0 & PK_S) | ((x3 << 11) & PK_M);
  p1 = x1 | (w1 & PK_S) | ((x3 << 7) & PK_M);
  p2 = x2 | (w2 & PK_S) | ((x3 << 3) & 0x38003800u) | ((w3 >> 1) & 0x40004000u);
}
__device__ __forceinline__ void unpack4_store(uint32_t addr, uint32_t p0, uint32_t p1, uint32_t p2, uint32_t thr) {
  const uint32_t x3 = ((p0 >> 11) & 0x000f000fu) | ((p1 >> 7) & 0x00f000f0u) | ((p2 >> 3) & 0x07000700u);
  sts128(addr, (p0 & ~PK_M) + __vminu2(p0 & 0x07ff07ffu, 0x00010001u) * thr,
         (p1 & ~PK_M) + __vminu2(p1 & 0x07ff07ffu, 0x00010001u) * thr,
         (p2 & ~PK_M) + __vminu2(p2 & 0x07ff07ffu, 0x00010001u) * thr,
         (x3 | ((p2 << 1) & PK_S)) + __vminu2(x3, 0x00010001u) * thr);
}
__device__ __forceinline__ uint32_t neg_base(uint32_t b) { return ((0u - (b << 7)) & 0xffffu) * 0x00010001u; }

__device__ __forceinline__ void pack_tile(uint32_t (&p)[48], uint32_t img, int lane, uint32_t bases) {
  const uint32_t nk = neg_base(bases & 0xffu), nv = neg_base((bases >> 8) & 0xffu);
#pragma unroll
  for (int i = 0; i < 16; i++) {
    uint32_t w0, w1, w2, w3;
    lds128(w0, w1, w2, w3, img + lane * 16 + i * 512);
    pack4(p[3 * i], p[3 * i + 1], p[3 * i + 2], w0, w1, w2, w3, i < 8 ? nk : nv);
  }
}
__device__ __forceinline__ void unpack_tile(const uint32_t (&p)[48], uint32_t img, int lane, uint32_t bases) {
  const uint32_t tk = (bases & 0xffu) << 7, tv = ((bases >> 8) & 0xffu) << 7;
#pragma unroll
  for (int i = 0; i < 16; i++)
    unpack4_store(img + lane * 16 + i * 512, p[3 * i], p[3 * i + 1], p[3 * i + 2], i < 8 ? tk : tv);
}
__device__ __forceinline__ void pack_tile_smem(uint32_t pk, uint32_t pv, uint32_t img, int lane, uint32_t bases) {
#pragma unroll 1
  for (int h = 0; h < 2; h++) {
    const uint32_t nb = neg_base((bases >> (8 * h)) & 0xffu);
    const uint32_t src = img + h * 4096 + lane * 16, dst = (h ? pv : pk) + lane * 4;
#pragma unroll
    for (int i = 0; i < 8; i++) {
      uint32_t w0, w1, w2, w3, p0, p1, p2;
      lds128(w0, w1, w2, w3, src + i * 512);
      pack4(p0, p1, p2, w0, w1, w2, w3, nb);
      sts32(dst + i * 384, p0); sts32(dst + i * 384 + 128, p1); sts32(dst + i * 384 + 256, p2);
    }
  }
}
__device__ __forceinline__ void unpack_tile_smem(uint32_t pk, uint32_t pv, uint32_t img, int lane, uint32_t bases) {
#pragma unroll 1
  for (int h = 0; h < 4; h++) {
    const uint32_t thr = ((bases >> (8 * (h >> 1))) & 0xffu) << 7;
    const uint32_t dst = img + h * 2048 + lane * 16, src = ((h & 2) ? pv : pk) + (h & 1) * 1536 + lane * 4;
    uint32_t p[12];
#pragma unroll
    for (int i = 0; i < 12; i++) p[i] = lds32(src + i * 128);
    __syncwarp();
#pragma unroll
    for (int i = 0; i < 4; i++) unpack4_store(dst + i * 512, p[3 * i], p[3 * i + 1], p[3 * i + 2], thr);
  }
}

template <int H>
__device__ __forceinline__ void w_frags(uint32_t (&A)[32], uint32_t seg, int lane) {
  const int row = (lane & 7) + ((lane >> 4) << 3);
  const uint32_t base = seg + row * 64 + ((((lane >> 3) & 1) ^ ((row >> 1) & 3)) << 4);
#pragma unroll
  for (int i = 0; i < 4; i++)
    ldsm4t(A[16 * H + 4 * i], A[16 * H + 4 * i + 1], A[16 * H + 4 * i + 2], A[16 * H + 4 * i + 3],
           (base ^ ((i & 1) << 5)) + (i >> 1) * 1024);
}

template <int NKS, bool LN, int FMT>
__device__ __forceinline__ void gemv_regs(const uint32_t (&A)[32], uint32_t sb, int warp, int lane, uint32_t xw,
                                          uint32_t* dst, bool real) {
  float acc[2][4] = {{0.f, 0.f, 0.f, 0.f}, {0.f, 0.f, 0.f, 0.f}};
  const int t = lane & 3, g = lane >> 2;
  float s1 = lo16(xw) + hi16(xw), s2 = fmaf(lo16(xw), lo16(xw), hi16(xw) * hi16(xw));
#pragma unroll
  for (int ks = 0; ks < NKS; ks++) {
    const uint32_t x0 = __shfl_sync(0xffffffffu, xw, 8 * ks + t);
    const uint32_t x1 = __shfl_sync(0xffffffffu, xw, 8 * ks + 4 + t);
    const uint32_t b0 = (LN && (g & 1)) ? 0x3f803f80u : x0, b1 = (LN && (g & 1)) ? 0x3f803f80u : x1;
    mma(acc[0], A[8 * ks], A[8 * ks + 1], A[8 * ks + 2], A[8 * ks + 3], b0, b1);
    mma(acc[1], A[8 * ks + 4], A[8 * ks + 5], A[8 * ks + 6], A[8 * ks + 7], b0, b1);
    if (LN) {
      s1 += __shfl_xor_sync(0xffffffffu, s1, 16 >> ks);
      s2 += __shfl_xor_sync(0xffffffffu, s2, 16 >> ks);
    }
  }
  if (LN) {
    s1 += __shfl_xor_sync(0xffffffffu, s1, 1);
    s2 += __shfl_xor_sync(0xffffffffu, s2, 1);
  }
  const float v = (t & 2) ? ((t & 1) ? acc[1][2] : acc[1][0]) : ((t & 1) ? acc[0][2] : acc[0][0]);
  if (LN) {
    const float cs = (t & 2) ? ((t & 1) ? acc[1][3] : acc[1][1]) : ((t & 1) ? acc[0][3] : acc[0][1]);
    stsf2(sb + SM_Q + (warp * 32 + 8 * t + g) * 8, v, cs);
    if (lane == 0) stsf2(sb + SM_STAT + warp * 8, s2, s1);
  } else {
    stsf(sb + SM_Q + (warp * 32 + 8 * t + g) * 4, v);
  }
  dst = pin(dst);
  uint32_t ra = sb + SM_Q + lane * (LN ? 8 : 4);
  asm volatile("" : "+r"(ra));
  __syncthreads();
  if (warp == 0) {
    float y;
    if (LN) {
      float u[8], c[8], q[8], m[8];
#pragma unroll
      for (int w = 0; w < 8; w++) ldsf2(q[w], m[w], sb + SM_STAT + w * 8);
#pragma unroll
      for (int w = 0; w < 8; w++) ldsf2(u[w], c[w], ra + w * 256);
      const float mean = (((m[0] + m[1]) + (m[2] + m[3])) + ((m[4] + m[5]) + (m[6] + m[7]))) * (1.f / 512.f);
      const float msq = (((q[0] + q[1]) + (q[2] + q[3])) + ((q[4] + q[5]) + (q[6] + q[7]))) * (1.f / 512.f);
      const float vb = rbf(fmaxf(fmaf(-mean, mean, msq), 0.f));
      float sq, rs;
      asm("sqrt.approx.ftz.f32 %0, %1;" : "=f"(sq) : "f"(rbf(vb + 1e-5f)));
      asm("rcp.approx.ftz.f32 %0, %1;" : "=f"(rs) : "f"(rbf(sq)));
      y = ((u[0] + u[1]) + (u[2] + u[3])) + ((u[4] + u[5]) + (u[6] + u[7]));
      const float cs = ((c[0] + c[1]) + (c[2] + c[3])) + ((c[4] + c[5]) + (c[6] + c[7]));
      y = fmaf(-rbf(mean), cs, y) * rs;
    } else {
      float u[8];
#pragma unroll
      for (int w = 0; w < 8; w++) u[w] = ldsf(ra + w * 128);
      y = ((u[0] + u[1]) + (u[2] + u[3])) + ((u[4] + u[5]) + (u[6] + u[7]));
    }
    uint32_t o;
    if (FMT == 2) o = pack2(y, __shfl_down_sync(0xffffffffu, y, 1));
    else o = __float_as_uint(FMT == 1 ? rbf(y) : y);
    o = enc(o);
    asm volatile("{.reg .pred p; setp.ne.u32 p, %2, 0; @p st.relaxed.gpu.global.u32 [%0], %1;}"
                 ::"l"(dst), "r"(o), "r"((uint32_t)(real && (FMT != 2 || !(lane & 1)))) : "memory");
  }
}

template <int NP, class F, class G>
__device__ __forceinline__ uint32_t add_partials(const uint32_t* p, uint32_t xw, bool real, F side, G after) {
  uint32_t a[NP], b[NP];
#pragma unroll
  for (int k = 0; k < NP; k++) a[k] = b[k] = 0u;
  int it = 0;
  bool pend, done = false;
  if (real) do {
#pragma unroll
    for (int k = 0; k < NP; k++)
      if (a[k] == 0u || b[k] == 0u) ldr64(a[k], b[k], p + k * 512);
    if (!done) done = side();
    pend = false;
#pragma unroll
    for (int k = 0; k < NP; k++) pend |= (a[k] == 0u || b[k] == 0u);
    if (!done) done = side();
    if (++it > SPIN_LIMIT) __trap();
  } while (__any_sync(0xffffffffu, pend) || !done);
  float y0 = 0.f, y1 = 0.f;
#pragma unroll
  for (int k = 0; k < NP; k++) { y0 += __uint_as_float(a[k]); y1 += __uint_as_float(b[k]); }
  asm volatile("" : "+f"(y0), "+f"(y1));
  after();
  return pack2(lo16(xw) + rbf(y0), hi16(xw) + rbf(y1));
}

__global__ void __launch_bounds__(NTHR, 1)
decode_kernel(const __grid_constant__ Maps maps, const uint32_t* __restrict__ x_in,
              const char* __restrict__ Kp, const char* __restrict__ Vp, uint32_t* __restrict__ out) {
  extern __shared__ __align__(1024) unsigned char smem[];
  const uint32_t sb = (uint32_t)__cvta_generic_to_shared(smem);
  const int tid = threadIdx.x, lane = tid & 31;
  const int warp = __shfl_sync(0xffffffffu, tid >> 5, 0);
  const int cta = blockIdx.x;
  const uint32_t t_start = __shfl_sync(0xffffffffu, (uint32_t)clock(), 0);
  const int head_lo = cta < 128 ? ((cta + 3 * (cta >> 3)) & 7) : 2 * (cta - 128), head_hi = cta < 128 ? head_lo : head_lo + 1;
  const int head = warp < 4 ? head_lo : head_hi;
  const int jw = cta < 128 ? (cta >> 3) * 8 + warp : 128 + (warp & 3);
  const uint32_t ring = sb + warp * WARP_BYTES;
  const uint32_t rbar = sb + SM_BAR + warp * 40;
  const uint32_t wbar = rbar + 24;
  const uint32_t wseg = ring + O_W;

  auto w_issue = [&](int half, const CUtensorMap* m, int col, int row) {
    if (lane == 0) {
      mbar_expect(wbar + half * 8, 2048);
      tma2d(wseg + half * 2048, m, col, row, wbar + half * 8, pol_evict_first());
    }
    __syncwarp();
  };
  auto issue_demote = [&](int sl, int t) {
    if (lane == 0) {
      uint64_t pn;
      asm volatile("createpolicy.fractional.L2::evict_normal.b64 %0, 1.0;" : "=l"(pn));
      const uint64_t pf = pol_evict_first();
      const int row = head * SK + t * 16;
      const uint32_t dst = ring + sl * SLOT_BYTES, b = rbar + sl * 8;
      mbar_expect(b, SLOT_BYTES);
      tma3d(dst, &maps.k, row, b, pn);
      asm volatile("cp.async.bulk.prefetch.L2.global.L2::cache_hint [%0], %1, %2;" ::"l"(Kp + (size_t)row * 256), "r"(4096), "l"(pf) : "memory");
      tma3d(dst + 4096, &maps.v, row, b, pn);
      asm volatile("cp.async.bulk.prefetch.L2.global.L2::cache_hint [%0], %1, %2;" ::"l"(Vp + (size_t)row * 256), "r"(4096), "l"(pf) : "memory");
    }
    __syncwarp();
  };
  auto issue = [&](int sl, int t, bool kp) {
    if (lane == 0) {
      const uint64_t pf = pol_evict_first();
      const int row = head * SK + t * 16;
      const uint32_t dst = ring + sl * SLOT_BYTES, b = rbar + sl * 8;
      mbar_expect(b, SLOT_BYTES);
      tma3d(dst, &maps.k, row, b, pf);
      if (kp) l2_prefetch(Kp + (size_t)row * 256, 4096);
      tma3d(dst + 4096, &maps.v, row, b, pf);
      if (kp) l2_prefetch(Vp + (size_t)row * 256, 4096);
    }
    __syncwarp();
  };
  auto stack_tile = [&](uint32_t r) -> int { return r == 5 ? 6 * WPH + (jw >> 1) : jw + (r == 6 ? 5 : (int)r) * WPH; };

  TS(0);
  uint32_t xw = __ldg(x_in + tid);
  if (lane == 0) {
    if (sb & 1023) __trap();
#pragma unroll
    for (int i = 0; i < 5; i++) mbar_init(rbar + i * 8, 1);
    asm volatile("fence.mbarrier_init.release.cluster;" ::: "memory");
    fence_async();
  }
  if (cta < 128) { w_issue(0, &maps.wq, cta * 32, warp * 64); w_issue(1, &maps.wq, cta * 32, warp * 64 + 32); }
  issue_demote(2, jw);
  if (tid == 32) {
    asm volatile("prefetch.tensormap [%0];" ::"l"(&maps.wo) : "memory");
    asm volatile("prefetch.tensormap [%0];" ::"l"(&maps.wg) : "memory");
    asm volatile("prefetch.tensormap [%0];" ::"l"(&maps.wu) : "memory");
    asm volatile("prefetch.tensormap [%0];" ::"l"(&maps.wd) : "memory");
  }
  __syncwarp();
  TS(21);

  uint32_t c0[48], c1[48], c2[48], c3[48];
#pragma unroll
  for (int i = 0; i < 48; i++) { c0[i] = 0; c1[i] = 0; c2[i] = 0; c3[i] = 0; }
  uint32_t exc = 0;

  uint32_t sst = 0;

  for (int layer = -1; layer < 2; layer++) {
    const bool live = layer >= 0;
    const int ly = live ? layer : 0;

    if (live) {
      Attn st;
#pragma unroll
      for (int i = 0; i < 4; i++) { st.o[i][0] = st.o[i][1] = st.o[i][2] = st.o[i][3] = 0.f; }
      st.m0 = st.m1 = -INFINITY; st.l0 = st.l1 = 0.f;
      const int ln = fresh_lane();
      const uint32_t koff = ((ln & 7) + ((ln >> 3) & 1) * 8) * 128 + (((ln >> 4) ^ (ln & 7)) << 4);
      const uint32_t voff = 4096 + (ln >> 4) * 2048 + (ln & 7) * 128 + ((((ln >> 3) & 1) ^ (ln & 7)) << 4);
      const uint32_t qaddr = sb + SM_Q + ((head - head_lo) * 4 + (ln & 3)) * Q_PITCH + (ln >> 3) * 16;
      const bool lowg = ln < 16;
      int nxt = jw - NSTAT * WPH;
      if (layer == 0) { sst = 7; nxt += WPH; }
      else sst = ((sst ^ 0x10) & 0x3ff0770) | 1;
      while (true) {
        int sl = -1;
        if ((sst & 2) && mbar_test(rbar + 8, (sst >> 5) & 1)) sl = 1;
        if (sst & 4) sl = 2;
        if ((sst & 1) && mbar_test(rbar, (sst >> 4) & 1)) sl = 0;
        sl = __shfl_sync(0xffffffffu, sl, 0);
        if (sl >= 0) {
          tile_smem(st, ring + sl * SLOT_BYTES + koff, ring + sl * SLOT_BYTES + voff, qaddr, lowg);
          __syncwarp();
          sst ^= 0x11u << sl;
          if (sl == 0) sst |= 0x2000;
          if (layer == 0) {
            if (sl != 0 || (sst & 0x8000)) {
              const int l_ = fresh_lane();
              const uint32_t r = (sst >> 8) & 7, img = ring + sl * SLOT_BYTES;
              uint32_t bases, cnt = (sst >> 21) & 31;
              if (!pack_prepare(img, l_, r, bases, exc, cnt)) bases |= 0x10000;
              sst = ((sst & ~(31u << 21) & ~0x8000u) | (cnt << 21)) + ((r == 4 && (warp & 1)) ? 0x200 : 0x100);
              if (l_ == EXC_CAP + (int)r) exc = bases;
              if (r == 0) pack_tile(c0, img, l_, bases);
              else if (r == 1) pack_tile(c1, img, l_, bases);
              else if (r == 2) pack_tile(c2, img, l_, bases);
              else if (r == 3) pack_tile(c3, img, l_, bases);
              else {
                const uint32_t pk = ring + (r == 4 ? O_C1 : r == 5 ? O_E : O_C0);
                pack_tile_smem(pk, pk + (r == 5 ? WARP_BYTES : 3072), img, l_, bases);
              }
              fence_async();
              __syncwarp();
              if (sl == 1 && (sst & 0x700) < 0x600) { issue(1, stack_tile((sst >> 8) & 7), false); sst |= 2; }
            }
          } else if (sl == 1 && ((sst >> 16) & 31)) {
            sst -= 1u << 16;
            uint32_t t;
            asm volatile("ld.shared.u16 %0, [%1];" : "=r"(t) : "r"(sb + SM_LIST + warp * (KCAP * 2) + ((sst >> 16) & 31) * 2) : "memory");
            issue(1, t, false); sst |= 2;
          }
        } else if (layer == 1 && (sst & 0x700) && !(sst & 2) && ((sst & 0x2000) || !(sst & 1))) {
          const int l_ = fresh_lane();
          const uint32_t r = ((sst >> 8) & 7) - 1, img = ring + SLOT_BYTES;
          sst = ((sst - ((r == 6 && (warp & 1)) ? 0x200 : 0x100)) | 2) & ~0x2000u;
          const uint32_t hdr = __shfl_sync(0xffffffffu, exc, EXC_CAP + r);
          if (hdr & 0x10000) {
            issue(1, stack_tile(r), false);
          } else {
            if (r == 0) unpack_tile(c0, img, l_, hdr);
            else if (r == 1) unpack_tile(c1, img, l_, hdr);
            else if (r == 2) unpack_tile(c2, img, l_, hdr);
            else if (r == 3) unpack_tile(c3, img, l_, hdr);
            else {
              const uint32_t pk = ring + (r == 4 ? O_C1 : r == 5 ? O_E : O_C0);
              unpack_tile_smem(pk, pk + (r == 5 ? WARP_BYTES : 3072), img, l_, hdr);
            }
            __syncwarp();
            if (l_ < (int)((sst >> 21) & 31) && ((exc >> 12) & 7) == r)
              asm volatile("st.shared.u16 [%0], %1;" ::"r"(img + (exc & 0xfffu) * 2), "r"(exc >> 16) : "memory");
            fence_async();
            __syncwarp();
            if (l_ == 0) mbar_expect(rbar + 8, 0);
          }
          __syncwarp();
          if ((sst & 0x700) == 0) TS(28);
        } else if (warp == 7 && (sst & 0x88) == 8) {
          sst = (sst | 0x80) & ~0x2000u;
          const int l_ = fresh_lane(), c_ = opaque(cta), y_ = opaque(ly);
          const uint4 z = make_uint4(0, 0, 0, 0);
          const int s_lo = c_ >> 3;
          uint4* po = reinterpret_cast<uint4*>(&g_s.PO[y_][head_lo][s_lo][0]);
          po[l_] = z; po[l_ + 32] = z;
          if (l_ < 2) reinterpret_cast<uint4*>(&g_s.ML[y_][head_lo][s_lo][0])[l_] = z;
          if (head_hi != head_lo) {
            po = reinterpret_cast<uint4*>(&g_s.PO[y_][head_hi][16][0]);
            po[l_] = z; po[l_ + 32] = z;
            if (l_ < 2) reinterpret_cast<uint4*>(&g_s.ML[y_][head_hi][16][0])[l_] = z;
          }
          if (c_ < 128) {
            (&g_s.Y1[y_][0][0])[c_ * 32 + l_] = 0;
            if (y_ == 0 && l_ < 16) g_s.QX[1][c_ * 16 + l_] = 0;
          }
          if (c_ < 112) { g_s.GU[y_][c_ * 32 + l_] = 0; (&g_s.Y2[y_][0][0])[c_ * 32 + l_] = 0; }
          if (c_ < 8 && y_ == 0 && l_ == 0) g_s.ctr[1][c_][0] = 0;
          __syncwarp();
          if (l_ == 0) {
            asm volatile("fence.acq_rel.gpu;" ::: "memory");
            const uint32_t old = atomicAdd(&g_s.cnt[y_][0], 1u);
            sts32(sb + SM_STAT + 64, (old / NCTA + 1) * NCTA);
          }
          __syncwarp();
        } else if ((sst & 7) == 0) {
          break;
        } else if ((sst & 0x3080) == 0x2080) {
          uint32_t target, c;
          asm volatile("ld.shared.u32 %0, [%1];" : "=r"(target) : "r"(sb + SM_STAT + 64) : "memory");
          asm volatile("ld.acquire.gpu.global.u32 %0, [%1];" : "=r"(c) : "l"(&g_s.cnt[opaque(ly)][0]) : "memory");
          sst &= ~0x2000u;
          if (__all_sync(0xffffffffu, (int)(c - target) >= 0)) sst |= 0x1000;
        } else if (__any_sync(0xffffffffu, (uint32_t)clock() - t_start > 0xc0000000u)) {
          __trap();
        }
        if (!(sst & 0x801)) {
          if (layer == 0 && (sst & 0x700) == 0x600) {
            issue(0, stack_tile(6), false); sst |= 0x8001;
          } else {
            const int d = __shfl_sync(0xffffffffu, nxt, 8) + NSTAT * WPH;
            const int nd = layer == 0 ? N_ALL : N_DYN;
            if (d >= nd - RESET_X) sst |= 8;
            if (d < nd) {
              const bool kp = d >= N_DYN;
              issue(0, T_DYN + d, kp); sst |= 1;
              if (kp) {
                if (lane == 0)
                  asm volatile("st.shared.u16 [%0], %1;" ::"r"(sb + SM_LIST + warp * (KCAP * 2) + ((sst >> 16) & 31) * 2), "r"(T_DYN + d) : "memory");
                sst += 1u << 16;
              }
              const bool full = (layer == 0 && ((sst >> 16) & 31) == KCAP) || (((STOP_M >> warp) & 1) && d >= (layer == 0 ? N_ALL - STOP_X0 : N_DYN - STOP_X1)), stat = d < (NSTAT - 1) * WPH;
              nxt = full ? 1 << 20 : d - (NSTAT - 1) * WPH;
              asm volatile("{.reg .pred p; setp.ne.u32 p, %2, 0; @p atom.global.relaxed.gpu.inc.u32 %0, [%1], 0x7fffffff;}"
                           : "+r"(nxt) : "l"(&g_s.ctr[layer][head][0]), "r"((uint32_t)(lane == 8 && !full && !stat)) : "memory");
              __syncwarp();
            } else if (layer == 1) {
              sst |= 0x800;
            } else if ((sst & 0x700) == 0x700) {
              issue(0, T_LAST + jw, false); sst |= 0x801;
            }
          }
        }
      }
      TS(2 + 10 * layer);
      int rank = __shfl_sync(0xffffffffu, nxt, 8) + NSTAT * WPH - (layer == 0 ? N_ALL : N_DYN);

      {
#pragma unroll
        for (int o = 4; o <= 16; o <<= 1) {
          st.l0 += __shfl_xor_sync(0xffffffffu, st.l0, o);
          st.l1 += __shfl_xor_sync(0xffffffffu, st.l1, o);
        }
        const int g = lane >> 2, t = lane & 3;
        const uint32_t a = ring + O_P + ((t & 1) * 128 + (t >> 1) * 64) * 4;
#pragma unroll
        for (int mt = 0; mt < 4; mt++) {
          sts32(a + ((16 * mt + g) ^ (8 * t)) * 4, pack2(st.o[mt][0], st.o[mt][1]));
          sts32(a + ((16 * mt + 8 + g) ^ (8 * t)) * 4, pack2(st.o[mt][2], st.o[mt][3]));
        }
        if (lane < 2)
          sts128(sb + SM_ML + warp * 32 + lane * 16, __float_as_uint(st.m0), __float_as_uint(st.l0),
                 __float_as_uint(st.m1), __float_as_uint(st.l1));
      }
      {
        const int hp = tid >> 7, d = tid & 127, odd = tid & 1, hq = 2 * hp + odd;
        uint32_t* ppo = pin(&g_s.PO[ly][head_lo][cta >> 3][hq * 64 + (d >> 1)]);
        uint32_t* pml = pin(&g_s.ML[ly][head_lo][cta >> 3][2 * hq]);
        uint32_t am = sb + SM_ML + hp * 16 + odd * 8;
        uint32_t ap = sb + O_P + (hp * 128 + ((d & ~1) ^ (8 * (hp + 2 * (d >> 6))))) * 4;
        uint32_t sel = odd ? 0x7632 : 0x5410;
        asm volatile("" : "+r"(am), "+r"(ap), "+r"(sel));
        if (cta < 128) {
          if (rank > 100000) rank = STOP_R;
          if (rank < WO_R0) {
            const uint32_t c0_ = clock();
            while (__any_sync(0xffffffffu, (uint32_t)clock() - c0_ < (uint32_t)((WO_R0 - rank) * WO_K))) {}
          }
          w_issue(0, &maps.wo, (cta & 15) * 32, (cta >> 4) * 512 + warp * 64);
        }
        __syncthreads();
        float mw[8], lw[8];
        uint32_t u[8];
#pragma unroll
        for (int w = 0; w < 8; w++) ldsf2(mw[w], lw[w], am + w * 32);
#pragma unroll
        for (int w = 0; w < 8; w++) {
          uint32_t x0, x1;
          asm volatile("ld.shared.v2.u32 {%0,%1}, [%2];" : "=r"(x0), "=r"(x1) : "r"(ap + w * WARP_BYTES) : "memory");
          u[w] = __byte_perm(x0, x1, sel);
        }
        const bool split = head_hi != head_lo;
        float Ma = fmaxf(fmaxf(mw[0], mw[1]), fmaxf(mw[2], mw[3]));
        float Mb = fmaxf(fmaxf(mw[4], mw[5]), fmaxf(mw[6], mw[7]));
        if (!split) Ma = Mb = fmaxf(Ma, Mb);
        float La = 0.f, a0 = 0.f, a1 = 0.f, Lb = 0.f, b0 = 0.f, b1 = 0.f;
#pragma unroll
        for (int w = 0; w < 4; w++) {
          const float ea = ex2(mw[w] - Ma), eb = ex2(mw[w + 4] - Mb);
          La = fmaf(lw[w], ea, La); a0 = fmaf(lo16(u[w]), ea, a0); a1 = fmaf(hi16(u[w]), ea, a1);
          Lb = fmaf(lw[w + 4], eb, Lb); b0 = fmaf(lo16(u[w + 4]), eb, b0); b1 = fmaf(hi16(u[w + 4]), eb, b1);
        }
        if (!split) { La += Lb; a0 += b0; a1 += b1; }
        if (d < 2) str64(pml, enc(__float_as_uint(Ma)), enc(__float_as_uint(La)));
        const float ia = rcp(La);
        str32(ppo, enc(pack2(a0 * ia, a1 * ia)));
        if (split) {
          if (d < 2) str64(pml + 17 * 8, enc(__float_as_uint(Mb)), enc(__float_as_uint(Lb)));
          const float ib = rcp(Lb);
          str32(ppo + 17 * 256, enc(pack2(b0 * ib, b1 * ib)));
        }
      }
      if (cta < 128) w_issue(1, &maps.wo, (cta & 15) * 32, (cta >> 4) * 512 + warp * 64 + 32);
      TS(31);
      if (tid == 255 && !(sst & 0x1000)) {
        uint32_t target, c;
        asm volatile("ld.shared.u32 %0, [%1];" : "=r"(target) : "r"(sb + SM_STAT + 64) : "memory");
        int it = 0;
        do {
          asm volatile("ld.acquire.gpu.global.u32 %0, [%1];" : "=r"(c) : "l"(&g_s.cnt[ly][0]) : "memory");
          if (++it > SPIN_LIMIT) __trap();
        } while ((int)(c - target) < 0);
      }
      __syncwarp();
      __syncthreads();
      TS(3 + 10 * layer);
    }

    if (cta < 128) {
      uint32_t A[32];
      if (live) {
#pragma unroll 1
        for (int real = 0; real < 2; real++) {
#pragma unroll
          for (int i = 0; i < 16; i++) A[i] = 0u;
          const int rb = cta >> 4;
          const uint32_t* pp = pin(&g_s.PO[ly][rb][0][tid]);
          const uint32_t* pm = pin(&g_s.ML[ly][rb][lane < 17 ? lane : 0][2 * (warp >> 1)]);
          uint32_t v[17], um = 0u, ul = 0u;
#pragma unroll
          for (int s = 0; s < 17; s++) v[s] = 0u;
          int it = 0;
          bool pend, done = false;
          if (real) {
            do {
              if (um == 0u || ul == 0u) ldr64(um, ul, pm);
#pragma unroll
              for (int s = 0; s < 17; s++)
                if (v[s] == 0u) v[s] = ldr32(pp + s * 256);
              if (!done && __all_sync(0xffffffffu, mbar_test(wbar, 1))) {
                w_frags<0>(A, wseg, lane);
                __syncwarp();
                if (cta < 112) w_issue(0, cta < 56 ? &maps.wg : &maps.wu, (cta < 56 ? cta : cta - 56) * 32, warp * 64);
                else if (layer == 0) w_issue(0, &maps.wq, cta * 32, warp * 64);
                done = true;
                if (layer == 0) TS(27);
              }
              pend = (um == 0u || ul == 0u);
#pragma unroll
              for (int s = 0; s < 17; s++) pend |= (v[s] == 0u);
              if (++it > SPIN_LIMIT) __trap();
            } while (__any_sync(0xffffffffu, pend) || !done);
            TS(4 + 10 * layer);
          }
          const float ms = __uint_as_float(um);
          int mi = __float_as_int(ms);
          mi = __reduce_max_sync(0xffffffffu, mi ^ ((mi >> 31) & 0x7fffffff));
          const float M = __int_as_float(mi ^ ((mi >> 31) & 0x7fffffff));
          const float e = lane < 17 ? __uint_as_float(ul) * ex2(ms - M) : 0.f;
          float L = 0.f, o0 = 0.f, o1 = 0.f, Lb = 0.f, p0 = 0.f, p1 = 0.f;
#pragma unroll
          for (int s = 0; s < 17; s++) {
            const float es = __shfl_sync(0xffffffffu, e, s);
            if (s & 1) { Lb += es; p0 = fmaf(es, lo16(v[s]), p0); p1 = fmaf(es, hi16(v[s]), p1); }
            else { L += es; o0 = fmaf(es, lo16(v[s]), o0); o1 = fmaf(es, hi16(v[s]), o1); }
          }
          o0 += p0; o1 += p1;
          asm volatile("" : "+f"(o0), "+f"(o1));
          if (real) mbar_wait(wbar + 8, cta < 112 ? layer ^ 1 : 1);
          w_frags<1>(A, wseg + 2048, lane);
          const float inv = rcp(L + Lb);
          gemv_regs<4, false, 0>(A, sb, warp, lane, pack2(o0 * inv, o1 * inv), &g_s.Y1[ly][0][0] + cta * 32 + lane, real);
          if (real) {
            if (cta < 112) w_issue(1, cta < 56 ? &maps.wg : &maps.wu, (cta < 56 ? cta : cta - 56) * 32, warp * 64 + 32);
            else if (layer == 0) w_issue(1, &maps.wq, cta * 32, warp * 64 + 32);
          }
          __syncthreads();
        }
        TS(5 + 10 * layer);
#pragma unroll 1
        for (int real = 0; real < 2; real++) {
#pragma unroll
          for (int i = 0; i < 16; i++) A[i] = 0u;
          const uint32_t xn = add_partials<8>(pin(&g_s.Y1[ly][0][2 * tid]), xw, real, [&]() {
            if (cta >= 112) return true;
            if (!__all_sync(0xffffffffu, mbar_test(wbar, 0))) return false;
            w_frags<0>(A, wseg, lane);
            __syncwarp();
            w_issue(0, &maps.wd, (cta & 15) * 32, (cta >> 4) * 256 + warp * 32);
            if (layer == 0) TS(29);
            return true;
          }, [&]() { if (real && cta < 112) mbar_wait(wbar + 8, layer); w_frags<1>(A, wseg + 2048, lane); });
          if (real) { xw = xn; TS(6 + 10 * layer); }
          if (cta < 112) {
            gemv_regs<4, true, 1>(A, sb, warp, lane, xn, &g_s.GU[ly][cta * 32 + lane], real);
            if (real) {
              if (layer == 0) {
                w_issue(1, &maps.wq, cta * 32, warp * 64 + 32);
              }
            }
            __syncthreads();
          }
        }
        if (cta < 112) {
          TS(7 + 10 * layer);
#pragma unroll 1
          for (int real = 0; real < 2; real++) {
#pragma unroll
            for (int i = 0; i < 16; i++) A[i] = 0u;
            const uint32_t* pg = pin(&g_s.GU[ly][(lane >> 4) * FF + (cta >> 4) * 256 + warp * 32 + (lane & 15) * 2]);
            uint32_t a = 0u, b = 0u;
            int it = 0;
            bool done = false;
            if (real) {
              do {
                if (a == 0u || b == 0u) ldr64(a, b, pg);
                if (!done && __all_sync(0xffffffffu, mbar_test(wbar, 1))) {
                  w_frags<0>(A, wseg, lane);
                  __syncwarp();
                  if (layer == 0) { w_issue(0, &maps.wq, cta * 32, warp * 64); TS(30); }
                  done = true;
                }
                if (++it > SPIN_LIMIT) __trap();
              } while (__any_sync(0xffffffffu, a == 0u || b == 0u) || !done);
              TS(8 + 10 * layer);
            }
            const float a0 = __uint_as_float(a), a1 = __uint_as_float(b);
            const float c0_ = __shfl_xor_sync(0xffffffffu, a0, 16), c1_ = __shfl_xor_sync(0xffffffffu, a1, 16);
            const float g0 = lane < 16 ? a0 : c0_, g1 = lane < 16 ? a1 : c1_;
            const float u0 = lane < 16 ? c0_ : a0, u1 = lane < 16 ? c1_ : a1;
            const uint32_t hw = pack2((g0 > 0.f ? g0 : g0 * 0.f) * u0, (g1 > 0.f ? g1 : g1 * 0.f) * u1);
            gemv_regs<2, false, 0>(A, sb, warp, lane, hw, &g_s.Y2[ly][0][0] + cta * 32 + lane, real);
            __syncthreads();
          }
          TS(9 + 10 * layer);
        }
        if (layer == 1 && cta != 127) break;
        if (layer == 0 && warp == 4) {
          if (lane < 16) g_s.QX[0][cta * 16 + lane] = 0;
          if (lane == 16 && cta < 8) g_s.ctr[0][cta][0] = 0;
          __syncwarp();
        }
      }
#pragma unroll 1
      for (int real = live ? 0 : 1; real < 2; real++) {
#pragma unroll
        for (int i = 0; i < 16; i++) A[i] = 0u;
        if (!live) {
          mbar_wait(wbar, 0); mbar_wait(wbar + 8, 0);
          w_frags<0>(A, wseg, lane);
          TS(24);
        }
        const uint32_t xn = add_partials<7>(pin(&g_s.Y2[ly][0][2 * tid]), xw, real && live, [&]() {
          if (layer == 1) return true;
          if (!__all_sync(0xffffffffu, mbar_test(wbar, 0) && mbar_test(wbar + 8, cta < 112 ? 1 : 0))) return false;
          w_frags<0>(A, wseg, lane);
          TS(26);
          return true;
        }, [&]() { w_frags<1>(A, wseg + 2048, lane); });
        if (real && live) {
          xw = xn;
          if (layer == 1) { out[tid] = xn; TS(20); return; }
          TS(10);
        }
        gemv_regs<4, true, 2>(A, sb, warp, lane, xw, &g_s.QX[(layer + 1) & 1][cta * 16 + (lane >> 1)], real);
        if (!real) __syncthreads();
      }
      if (live) TS(25);
    } else if (layer == 1) {
      break;
    }
    if (!live) {
      mbar_wait(rbar + 16, 0);
      issue_demote(1, jw + WPH);
    }
    __syncthreads();
    {
      const uint32_t* pq = &g_s.QX[layer + 1][head_lo * 256 + tid];
      uint32_t qv0 = 0u, qv1 = head_hi != head_lo ? 0u : 1u;
      int it = 0;
      do {
        if (qv0 == 0u) qv0 = ldr32(pq);
        if (qv1 == 0u) qv1 = ldr32(pq + 256);
        if (++it > SPIN_LIMIT) __trap();
      } while (__any_sync(0xffffffffu, qv0 == 0u || qv1 == 0u));
      if (!live) issue_demote(0, T_DYN + jw);
      sts32(sb + SM_Q + (tid >> 6) * Q_PITCH + (tid & 63) * 4, qv0);
      sts32(sb + SM_Q + (4 + (tid >> 6)) * Q_PITCH + (tid & 63) * 4, qv1);
    }
    __syncthreads();
    TS(layer < 0 ? 1 : 11);
  }
}

typedef CUresult (*EncodeFn)(CUtensorMap*, CUtensorMapDataType, cuuint32_t, void*, const cuuint64_t*,
                             const cuuint64_t*, const cuuint32_t*, const cuuint32_t*, CUtensorMapInterleave,
                             CUtensorMapSwizzle, CUtensorMapL2promotion, CUtensorMapFloatOOBfill);

void make_kv_map(EncodeFn enc, CUtensorMap* m, void* p) {
  cuuint64_t dims[3] = {64, (cuuint64_t)8 * SK, 2};
  cuuint64_t strides[2] = {256, 128};
  cuuint32_t box[3] = {64, 16, 2}, es[3] = {1, 1, 1};
  enc(m, CU_TENSOR_MAP_DATA_TYPE_BFLOAT16, 3, p, dims, strides, box, es, CU_TENSOR_MAP_INTERLEAVE_NONE,
      CU_TENSOR_MAP_SWIZZLE_128B, CU_TENSOR_MAP_L2_PROMOTION_NONE, CU_TENSOR_MAP_FLOAT_OOB_FILL_NONE);
}
void make_w_map(EncodeFn enc, CUtensorMap* m, void* p, int rows, int cols) {
  cuuint64_t dims[2] = {(cuuint64_t)cols, (cuuint64_t)rows};
  cuuint64_t strides[1] = {(cuuint64_t)cols * 2};
  cuuint32_t box[2] = {32, 32}, es[2] = {1, 1};
  enc(m, CU_TENSOR_MAP_DATA_TYPE_BFLOAT16, 2, p, dims, strides, box, es, CU_TENSOR_MAP_INTERLEAVE_NONE,
      CU_TENSOR_MAP_SWIZZLE_64B, CU_TENSOR_MAP_L2_PROMOTION_NONE, CU_TENSOR_MAP_FLOAT_OOB_FILL_NONE);
}

}

extern "C" void kernel_launch(void* const* d_in, const int* in_sizes, int n_in, void* d_out, int out_size) {
  (void)in_sizes; (void)n_in; (void)out_size;
  void* fn = nullptr;
  cudaDriverEntryPointQueryResult qr;
  cudaGetDriverEntryPoint("cuTensorMapEncodeTiled", &fn, cudaEnableDefault, &qr);
  EncodeFn enc = (EncodeFn)fn;
  Maps maps;
  make_kv_map(enc, &maps.k, d_in[1]);
  make_kv_map(enc, &maps.v, d_in[2]);
  make_w_map(enc, &maps.wq, d_in[3], DM, 4096);
  make_w_map(enc, &maps.wo, d_in[4], 4096, DM);
  make_w_map(enc, &maps.wg, d_in[6], DM, FF);
  make_w_map(enc, &maps.wu, d_in[7], DM, FF);
  make_w_map(enc, &maps.wd, d_in[8], FF, DM);
  cudaFuncSetAttribute(decode_kernel, cudaFuncAttributeMaxDynamicSharedMemorySize, SM_TOTAL);
  decode_kernel<<<NCTA, NTHR, SM_TOTAL, cudaStreamPerThread>>>(
      maps, (const uint32_t*)d_in[0], (const char*)d_in[1], (const char*)d_in[2], (uint32_t*)d_out);
}
```

```cpp
#include <cuda_runtime.h>
#include <cuda_bf16.h>
#include <cuda.h>
#include <stdint.h>

namespace {

constexpr int NCTA = 132, NWARP = 8, NTHR = 256;
constexpr int DM = 512, SK = 65536, FF = 1792;
constexpr int WPH = NCTA;
constexpr int SLOT_BYTES = 8192;
constexpr int KEEP_H = 760;
constexpr int RESET_X = 400;
constexpr int STOP_X = 700;
constexpr int WO_K = 25;
constexpr int WO_R0 = 60;
constexpr int STOP_R = -80;
constexpr int NSTAT = 4;
constexpr int T_DYN = 6 * 132 + 66;
constexpr int T_LAST = 4096 - 132;
constexpr int N_ALL = T_LAST - T_DYN;
constexpr int N_DYN = N_ALL - KEEP_H;
constexpr int KCAP = 12;
static_assert(KCAP * 99 > KEEP_H, "the warps that stream to the end must be able to take all kept tiles");
static_assert(N_DYN - STOP_X >= NSTAT * 132, "");

constexpr int WARP_BYTES = 28672;
constexpr int O_W = 8192, O_C0 = 12288, O_C1 = 18432, O_E = 24576, O_P = 27648;
constexpr int SM_BAR = NWARP * WARP_BYTES;
constexpr int SM_STAT = SM_BAR + 320;
constexpr int SM_Q = SM_STAT + 128;
constexpr int Q_PITCH = 272;
constexpr int SM_LIST = SM_Q + 2 * 4 * Q_PITCH;
constexpr int SM_ML = SM_LIST + NWARP * KCAP * 2;
constexpr int SM_TOTAL = SM_ML + NWARP * 32;
static_assert(SM_TOTAL <= 232448, "");

struct Scratch {
  uint32_t QX[2][2048];
  uint32_t PO[2][8][17][256];
  uint32_t ML[2][8][17][8];
  uint32_t Y1[2][8][512];
  uint32_t GU[2][2 * FF];
  uint32_t Y2[2][7][512];
  uint32_t cnt[2][32];
  uint32_t ctr[2][8][32];
};
__device__ __align__(1024) Scratch g_s;

struct Maps { CUtensorMap k, v, wq, wo, wg, wu, wd; };

constexpr int SPIN_LIMIT = 1 << 22;

__device__ __forceinline__ void mbar_init(uint32_t bar, int cnt) {
  asm volatile("mbarrier.init.shared::cta.b64 [%0], %1;" ::"r"(bar), "r"(cnt) : "memory");
}
__device__ __forceinline__ void mbar_expect(uint32_t bar, uint32_t bytes) {
  asm volatile("mbarrier.arrive.expect_tx.shared::cta.b64 _, [%0], %1;" ::"r"(bar), "r"(bytes) : "memory");
}
__device__ __forceinline__ void mbar_wait(uint32_t bar, uint32_t parity) {
  uint32_t ok;
  int it = 0;
  do {
    asm volatile("{.reg .pred p; mbarrier.try_wait.parity.shared::cta.b64 p, [%1], %2; selp.u32 %0,1,0,p;}"
                 : "=r"(ok) : "r"(bar), "r"(parity) : "memory");
    if (++it > SPIN_LIMIT) __trap();
  } while (!__all_sync(0xffffffffu, ok));
}
__device__ __forceinline__ bool mbar_test(uint32_t bar, uint32_t parity) {
  uint32_t ok;
  asm volatile("{.reg .pred p; mbarrier.test_wait.parity.shared::cta.b64 p, [%1], %2; selp.u32 %0,1,0,p;}"
               : "=r"(ok) : "r"(bar), "r"(parity) : "memory");
  return ok != 0;
}
__device__ __forceinline__ int fresh_lane() { int l; asm volatile("mov.u32 %0, %laneid;" : "=r"(l)); return l; }
template <class T> __device__ __forceinline__ T* pin(T* p) { asm volatile("" : "+l"(p)); return p; }
__device__ __forceinline__ int opaque(int x) { asm volatile("" : "+r"(x)); return x; }
__device__ __forceinline__ void tma3d(uint32_t dst, const CUtensorMap* m, int row, uint32_t bar, uint64_t pol) {
  asm volatile("cp.async.bulk.tensor.3d.shared::cluster.global.mbarrier::complete_tx::bytes.L2::cache_hint"
               " [%0], [%1, {%3, %4, %3}], [%2], %5;"
               ::"r"(dst), "l"(m), "r"(bar), "r"(0), "r"(row), "l"(pol) : "memory");
}
__device__ __forceinline__ void tma2d(uint32_t dst, const CUtensorMap* m, int col, int row, uint32_t bar, uint64_t pol) {
  asm volatile("cp.async.bulk.tensor.2d.shared::cluster.global.mbarrier::complete_tx::bytes.L2::cache_hint"
               " [%0], [%1, {%3, %4}], [%2], %5;"
               ::"r"(dst), "l"(m), "r"(bar), "r"(col), "r"(row), "l"(pol) : "memory");
}
__device__ __forceinline__ void l2_prefetch(const void* p, uint32_t bytes) {
  asm volatile("cp.async.bulk.prefetch.L2.global [%0], %1;" ::"l"(p), "r"(bytes) : "memory");
}
__device__ __forceinline__ uint64_t pol_evict_first() {
  uint64_t p;
  asm volatile("createpolicy.fractional.L2::evict_first.b64 %0, 1.0;" : "=l"(p));
  return p;
}
__device__ __forceinline__ void ldsm4(uint32_t& a, uint32_t& b, uint32_t& c, uint32_t& d, uint32_t addr) {
  asm volatile("ldmatrix.sync.aligned.m8n8.x4.shared.b16 {%0,%1,%2,%3}, [%4];"
               : "=r"(a), "=r"(b), "=r"(c), "=r"(d) : "r"(addr) : "memory");
}
__device__ __forceinline__ void ldsm4t(uint32_t& a, uint32_t& b, uint32_t& c, uint32_t& d, uint32_t addr) {
  asm volatile("ldmatrix.sync.aligned.m8n8.x4.trans.shared.b16 {%0,%1,%2,%3}, [%4];"
               : "=r"(a), "=r"(b), "=r"(c), "=r"(d) : "r"(addr) : "memory");
}
__device__ __forceinline__ void mma(float (&c)[4], uint32_t a0, uint32_t a1, uint32_t a2, uint32_t a3,
                                    uint32_t b0, uint32_t b1) {
  asm volatile("mma.sync.aligned.m16n8k16.row.col.f32.bf16.bf16.f32 {%0,%1,%2,%3}, {%4,%5,%6,%7}, {%8,%9}, {%0,%1,%2,%3};"
               : "+f"(c[0]), "+f"(c[1]), "+f"(c[2]), "+f"(c[3])
               : "r"(a0), "r"(a1), "r"(a2), "r"(a3), "r"(b0), "r"(b1));
}
__device__ __forceinline__ uint32_t movm(uint32_t a) {
  uint32_t d;
  asm volatile("movmatrix.sync.aligned.m8n8.trans.b16 %0, %1;" : "=r"(d) : "r"(a));
  return d;
}
__device__ __forceinline__ uint32_t pack2(float lo, float hi) {
  uint32_t d;
  asm("cvt.rn.bf16x2.f32 %0, %1, %2;" : "=r"(d) : "f"(hi), "f"(lo));
  return d;
}
__device__ __forceinline__ float lo16(uint32_t w) { return __uint_as_float(w << 16); }
__device__ __forceinline__ float hi16(uint32_t w) { return __uint_as_float(w & 0xffff0000u); }
__device__ __forceinline__ float rbf(float x) { return lo16(pack2(x, 0.f)); }
__device__ __forceinline__ float ex2(float x) {
  float y;
  asm("ex2.approx.ftz.f32 %0, %1;" : "=f"(y) : "f"(x));
  return y;
}
__device__ __forceinline__ float rcp(float x) {
  float y;
  asm("rcp.approx.ftz.f32 %0, %1;" : "=f"(y) : "f"(x));
  return y;
}
__device__ __forceinline__ uint32_t enc(uint32_t w) { return w ? w : 0x80000000u; }
__device__ __forceinline__ uint32_t ldr32(const uint32_t* p) {
  uint32_t v;
  asm volatile("ld.relaxed.gpu.global.u32 %0, [%1];" : "=r"(v) : "l"(p) : "memory");
  return v;
}
__device__ __forceinline__ void ldr64(uint32_t& a, uint32_t& b, const uint32_t* p) {
  asm volatile("ld.relaxed.gpu.global.v2.u32 {%0,%1}, [%2];" : "=r"(a), "=r"(b) : "l"(p) : "memory");
}
__device__ __forceinline__ void str32(uint32_t* p, uint32_t v) {
  asm volatile("st.relaxed.gpu.global.u32 [%0], %1;" ::"l"(p), "r"(v) : "memory");
}
__device__ __forceinline__ void str64(uint32_t* p, uint32_t a, uint32_t b) {
  asm volatile("st.relaxed.gpu.global.v2.u32 [%0], {%1,%2};" ::"l"(p), "r"(a), "r"(b) : "memory");
}
__device__ __forceinline__ void sts32(uint32_t addr, uint32_t v) {
  asm volatile("st.shared.u32 [%0], %1;" ::"r"(addr), "r"(v) : "memory");
}
__device__ __forceinline__ void stsf(uint32_t addr, float v) {
  asm volatile("st.shared.f32 [%0], %1;" ::"r"(addr), "f"(v) : "memory");
}
__device__ __forceinline__ void stsf2(uint32_t addr, float a, float b) {
  asm volatile("st.shared.v2.f32 [%0], {%1,%2};" ::"r"(addr), "f"(a), "f"(b) : "memory");
}
__device__ __forceinline__ float ldsf(uint32_t addr) {
  float v;
  asm volatile("ld.shared.f32 %0, [%1];" : "=f"(v) : "r"(addr) : "memory");
  return v;
}
__device__ __forceinline__ void ldsf2(float& a, float& b, uint32_t addr) {
  asm volatile("ld.shared.v2.f32 {%0,%1}, [%2];" : "=f"(a), "=f"(b) : "r"(addr) : "memory");
}
__device__ __forceinline__ void fence_async() { asm volatile("fence.proxy.async.shared::cta;" ::: "memory"); }

constexpr float SCALE_C = 0.08838834764831845f * 1.4426950408889634f;

struct Attn {
  float o[4][4];
  float m0, m1, l0, l1;
};

__device__ __forceinline__ void softmax_step(Attn& st, const float (&s)[4], uint32_t& r0, uint32_t& r1) {
  float t0 = fmaxf(s[0], s[2]), t1 = fmaxf(s[1], s[3]);
#pragma unroll
  for (int o = 4; o <= 16; o <<= 1) {
    t0 = fmaxf(t0, __shfl_xor_sync(0xffffffffu, t0, o));
    t1 = fmaxf(t1, __shfl_xor_sync(0xffffffffu, t1, o));
  }
  float n0 = fmaxf(st.m0, t0 * SCALE_C), n1 = fmaxf(st.m1, t1 * SCALE_C);
  float a0 = ex2(st.m0 - n0), a1 = ex2(st.m1 - n1);
  st.m0 = n0; st.m1 = n1;
  float p0 = ex2(fmaf(s[0], SCALE_C, -n0)), p1 = ex2(fmaf(s[1], SCALE_C, -n1));
  float p2 = ex2(fmaf(s[2], SCALE_C, -n0)), p3 = ex2(fmaf(s[3], SCALE_C, -n1));
  r0 = movm(pack2(p0, p1));
  r1 = movm(pack2(p2, p3));
  st.l0 = fmaf(st.l0, a0, p0 + p2);
  st.l1 = fmaf(st.l1, a1, p1 + p3);
#pragma unroll
  for (int i = 0; i < 4; i++) {
    st.o[i][0] *= a0; st.o[i][1] *= a1; st.o[i][2] *= a0; st.o[i][3] *= a1;
  }
}

__device__ __forceinline__ void tile_smem(Attn& st, uint32_t kaddr, uint32_t vaddr, uint32_t qaddr, bool lowg) {
  float s[4] = {0.f, 0.f, 0.f, 0.f}, s2[4] = {0.f, 0.f, 0.f, 0.f};
#pragma unroll
  for (int j = 0; j < 4; j++) {
    uint32_t q0, q1, q2, q3, a0, a1, a2, a3, c0, c1, c2, c3;
    ldsm4(q0, q1, q2, q3, qaddr + j * 64);
    ldsm4(a0, a1, a2, a3, (kaddr ^ (((2 * j) & 3) << 5)) + (j >> 1) * 2048);
    ldsm4(c0, c1, c2, c3, (kaddr ^ (((2 * j + 1) & 3) << 5)) + (j >> 1) * 2048);
    mma(s, a0, a1, a2, a3, q0, q1);
    mma(s2, c0, c1, c2, c3, q2, q3);
  }
#pragma unroll
  for (int i = 0; i < 4; i++) s[i] += s2[i];
  uint32_t r0, r1;
  softmax_step(st, s, r0, r1);
#pragma unroll
  for (int kg = 0; kg < 2; kg++) {
    uint32_t r = kg ? r1 : r0;
    uint32_t b0 = lowg ? r : 0u, b1 = lowg ? 0u : r;
#pragma unroll
    for (int mt = 0; mt < 4; mt++) {
      uint32_t a0, a1, a2, a3;
      ldsm4t(a0, a1, a2, a3, (vaddr ^ (mt << 5)) + kg * 1024);
      mma(st.o[mt], a0, a1, a2, a3, b0, b1);
    }
  }
}

__device__ __forceinline__ void lds128(uint32_t& a, uint32_t& b, uint32_t& c, uint32_t& d, uint32_t addr) {
  asm volatile("ld.shared.v4.u32 {%0,%1,%2,%3}, [%4];" : "=r"(a), "=r"(b), "=r"(c), "=r"(d) : "r"(addr) : "memory");
}
__device__ __forceinline__ void sts128(uint32_t addr, uint32_t a, uint32_t b, uint32_t c, uint32_t d) {
  asm volatile("st.shared.v4.u32 [%0], {%1,%2,%3,%4};" ::"r"(addr), "r"(a), "r"(b), "r"(c), "r"(d) : "memory");
}

constexpr uint32_t PK_M = 0x78007800u, PK_S = 0x80008000u;
constexpr int EXC_CAP = 25;

__device__ __forceinline__ uint32_t lds32(uint32_t addr) {
  uint32_t v;
  asm volatile("ld.shared.u32 %0, [%1];" : "=r"(v) : "r"(addr) : "memory");
  return v;
}

__device__ __forceinline__ bool pack_prepare(uint32_t img, int lane, int r, uint32_t& bases, uint32_t& exc, uint32_t& cnt) {
  bool ok = true;
  bases = 0;
  uint32_t c = cnt;
#pragma unroll 1
  for (int h = 0; h < 2; h++) {
    const uint32_t base = img + h * 4096 + lane * 16;
    uint32_t mx = 0u, mn = 0xffffffffu;
#pragma unroll
    for (int i = 0; i < 8; i++) {
      uint32_t w0, w1, w2, w3;
      lds128(w0, w1, w2, w3, base + i * 512);
      w0 &= ~PK_S; w1 &= ~PK_S; w2 &= ~PK_S; w3 &= ~PK_S;
      mx = __vimax3_u16x2(mx, w0, w1); mx = __vimax3_u16x2(mx, w2, w3);
      mn = __viaddmin_u16x2(w0, 0xffffffffu, mn); mn = __viaddmin_u16x2(w1, 0xffffffffu, mn);
      mn = __viaddmin_u16x2(w2, 0xffffffffu, mn); mn = __viaddmin_u16x2(w3, 0xffffffffu, mn);
    }
    const uint32_t e = __reduce_max_sync(0xffffffffu, max(mx & 0xffffu, mx >> 16)) >> 7;
    const uint32_t B = e > 15u ? e - 15u : 0u, thr = B << 7;
    bases |= B << (8 * h);
    uint32_t todo = __ballot_sync(0xffffffffu, min(mn & 0xffffu, mn >> 16) < thr);
    if (__popc(todo) > 8) ok = false;
    while (todo && ok) {
      const int src = __ffs(todo) - 1;
      todo &= todo - 1;
      const uint32_t off = h * 4096 + src * 16 + (lane >> 2) * 512 + (lane & 3) * 4;
      const uint32_t w = lds32(img + off);
#pragma unroll 1
      for (int j = 0; j < 2; j++) {
        const uint32_t v = j ? w >> 16 : w & 0xffffu;
        uint32_t m = __ballot_sync(0xffffffffu, (v & 0x7fffu) - 1u < thr);
        if (c + __popc(m) > EXC_CAP) { ok = false; break; }
        while (m) {
          const uint32_t en = __shfl_sync(0xffffffffu, (v << 16) | (r << 12) | ((off >> 1) + j), __ffs(m) - 1);
          m &= m - 1;
          if (lane == (int)c) exc = en;
          c++;
        }
      }
    }
  }
  if (ok) cnt = c;
  return ok;
}

__device__ __forceinline__ void pack4(uint32_t& p0, uint32_t& p1, uint32_t& p2, uint32_t w0, uint32_t w1, uint32_t w2,
                                      uint32_t w3, uint32_t nb) {
  const uint32_t x0 = __viaddmax_s16x2(w0 & ~PK_S, nb, 0u), x1 = __viaddmax_s16x2(w1 & ~PK_S, nb, 0u);
  const uint32_t x2 = __viaddmax_s16x2(w2 & ~PK_S, nb, 0u), x3 = __viaddmax_s16x2(w3 & ~PK_S, nb, 0u);
  p0 = x0 | (w0 & PK_S) | ((x3 << 11) & PK_M);
  p1 = x1 | (w1 & PK_S) | ((x3 << 7) & PK_M);
  p2 = x2 | (w2 & PK_S) | ((x3 << 3) & 0x38003800u) | ((w3 >> 1) & 0x40004000u);
}
__device__ __forceinline__ void unpack4_store(uint32_t addr, uint32_t p0, uint32_t p1, uint32_t p2, uint32_t thr) {
  const uint32_t x3 = ((p0 >> 11) & 0x000f000fu) | ((p1 >> 7) & 0x00f000f0u) | ((p2 >> 3) & 0x07000700u);
  sts128(addr, (p0 & ~PK_M) + __vminu2(p0 & 0x07ff07ffu, 0x00010001u) * thr,
         (p1 & ~PK_M) + __vminu2(p1 & 0x07ff07ffu, 0x00010001u) * thr,
         (p2 & ~PK_M) + __vminu2(p2 & 0x07ff07ffu, 0x00010001u) * thr,
         (x3 | ((p2 << 1) & PK_S)) + __vminu2(x3, 0x00010001u) * thr);
}
__device__ __forceinline__ uint32_t neg_base(uint32_t b) { return ((0u - (b << 7)) & 0xffffu) * 0x00010001u; }

__device__ __forceinline__ void pack_tile(uint32_t (&p)[48], uint32_t img, int lane, uint32_t bases) {
  const uint32_t nk = neg_base(bases & 0xffu), nv = neg_base((bases >> 8) & 0xffu);
#pragma unroll
  for (int i = 0; i < 16; i++) {
    uint32_t w0, w1, w2, w3;
    lds128(w0, w1, w2, w3, img + lane * 16 + i * 512);
    pack4(p[3 * i], p[3 * i + 1], p[3 * i + 2], w0, w1, w2, w3, i < 8 ? nk : nv);
  }
}
__device__ __forceinline__ void unpack_tile(const uint32_t (&p)[48], uint32_t img, int lane, uint32_t bases) {
  const uint32_t tk = (bases & 0xffu) << 7, tv = ((bases >> 8) & 0xffu) << 7;
#pragma unroll
  for (int i = 0; i < 16; i++)
    unpack4_store(img + lane * 16 + i * 512, p[3 * i], p[3 * i + 1], p[3 * i + 2], i < 8 ? tk : tv);
}
__device__ __forceinline__ void pack_tile_smem(uint32_t pk, uint32_t pv, uint32_t img, int lane, uint32_t bases) {
#pragma unroll 1
  for (int h = 0; h < 2; h++) {
    const uint32_t nb = neg_base((bases >> (8 * h)) & 0xffu);
    const uint32_t src = img + h * 4096 + lane * 16, dst = (h ? pv : pk) + lane * 4;
#pragma unroll
    for (int i = 0; i < 8; i++) {
      uint32_t w0, w1, w2, w3, p0, p1, p2;
      lds128(w0, w1, w2, w3, src + i * 512);
      pack4(p0, p1, p2, w0, w1, w2, w3, nb);
      sts32(dst + i * 384, p0); sts32(dst + i * 384 + 128, p1); sts32(dst + i * 384 + 256, p2);
    }
  }
}
__device__ __forceinline__ void unpack_tile_smem(uint32_t pk, uint32_t pv, uint32_t img, int lane, uint32_t bases) {
#pragma unroll 1
  for (int h = 0; h < 4; h++) {
    const uint32_t thr = ((bases >> (8 * (h >> 1))) & 0xffu) << 7;
    const uint32_t dst = img + h * 2048 + lane * 16, src = ((h & 2) ? pv : pk) + (h & 1) * 1536 + lane * 4;
    uint32_t p[12];
#pragma unroll
    for (int i = 0; i < 12; i++) p[i] = lds32(src + i * 128);
    __syncwarp();
#pragma unroll
    for (int i = 0; i < 4; i++) unpack4_store(dst + i * 512, p[3 * i], p[3 * i + 1], p[3 * i + 2], thr);
  }
}

template <int H>
__device__ __forceinline__ void w_frags(uint32_t (&A)[32], uint32_t seg, int lane) {
  const int row = (lane & 7) + ((lane >> 4) << 3);
  const uint32_t base = seg + row * 64 + ((((lane >> 3) & 1) ^ ((row >> 1) & 3)) << 4);
#pragma unroll
  for (int i = 0; i < 4; i++)
    ldsm4t(A[16 * H + 4 * i], A[16 * H + 4 * i + 1], A[16 * H + 4 * i + 2], A[16 * H + 4 * i + 3],
           (base ^ ((i & 1) << 5)) + (i >> 1) * 1024);
}

template <int NKS, bool LN, int FMT>
__device__ __forceinline__ void gemv_regs(const uint32_t (&A)[32], uint32_t sb, int warp, int lane, uint32_t xw,
                                          uint32_t* dst, bool real) {
  float acc[2][4] = {{0.f, 0.f, 0.f, 0.f}, {0.f, 0.f, 0.f, 0.f}};
  const int t = lane & 3, g = lane >> 2;
  float s1 = lo16(xw) + hi16(xw), s2 = fmaf(lo16(xw), lo16(xw), hi16(xw) * hi16(xw));
#pragma unroll
  for (int ks = 0; ks < NKS; ks++) {
    const uint32_t x0 = __shfl_sync(0xffffffffu, xw, 8 * ks + t);
    const uint32_t x1 = __shfl_sync(0xffffffffu, xw, 8 * ks + 4 + t);
    const uint32_t b0 = (LN && (g & 1)) ? 0x3f803f80u : x0, b1 = (LN && (g & 1)) ? 0x3f803f80u : x1;
    mma(acc[0], A[8 * ks], A[8 * ks + 1], A[8 * ks + 2], A[8 * ks + 3], b0, b1);
    mma(acc[1], A[8 * ks + 4], A[8 * ks + 5], A[8 * ks + 6], A[8 * ks + 7], b0, b1);
    if (LN) {
      s1 += __shfl_xor_sync(0xffffffffu, s1, 16 >> ks);
      s2 += __shfl_xor_sync(0xffffffffu, s2, 16 >> ks);
    }
  }
  if (LN) {
    s1 += __shfl_xor_sync(0xffffffffu, s1, 1);
    s2 += __shfl_xor_sync(0xffffffffu, s2, 1);
  }
  const float v = (t & 2) ? ((t & 1) ? acc[1][2] : acc[1][0]) : ((t & 1) ? acc[0][2] : acc[0][0]);
  if (LN) {
    const float cs = (t & 2) ? ((t & 1) ? acc[1][3] : acc[1][1]) : ((t & 1) ? acc[0][3] : acc[0][1]);
    stsf2(sb + SM_Q + (warp * 32 + 8 * t + g) * 8, v, cs);
    if (lane == 0) stsf2(sb + SM_STAT + warp * 8, s2, s1);
  } else {
    stsf(sb + SM_Q + (warp * 32 + 8 * t + g) * 4, v);
  }
  dst = pin(dst);
  uint32_t ra = sb + SM_Q + lane * (LN ? 8 : 4);
  asm volatile("" : "+r"(ra));
  __syncthreads();
  if (warp == 0) {
    float y;
    if (LN) {
      float u[8], c[8], q[8], m[8];
#pragma unroll
      for (int w = 0; w < 8; w++) ldsf2(q[w], m[w], sb + SM_STAT + w * 8);
#pragma unroll
      for (int w = 0; w < 8; w++) ldsf2(u[w], c[w], ra + w * 256);
      const float mean = (((m[0] + m[1]) + (m[2] + m[3])) + ((m[4] + m[5]) + (m[6] + m[7]))) * (1.f / 512.f);
      const float msq = (((q[0] + q[1]) + (q[2] + q[3])) + ((q[4] + q[5]) + (q[6] + q[7]))) * (1.f / 512.f);
      const float vb = rbf(fmaxf(fmaf(-mean, mean, msq), 0.f));
      float sq, rs;
      asm("sqrt.approx.ftz.f32 %0, %1;" : "=f"(sq) : "f"(rbf(vb + 1e-5f)));
      asm("rcp.approx.ftz.f32 %0, %1;" : "=f"(rs) : "f"(rbf(sq)));
      y = ((u[0] + u[1]) + (u[2] + u[3])) + ((u[4] + u[5]) + (u[6] + u[7]));
      const float cs = ((c[0] + c[1]) + (c[2] + c[3])) + ((c[4] + c[5]) + (c[6] + c[7]));
      y = fmaf(-rbf(mean), cs, y) * rs;
    } else {
      float u[8];
#pragma unroll
      for (int w = 0; w < 8; w++) u[w] = ldsf(ra + w * 128);
      y = ((u[0] + u[1]) + (u[2] + u[3])) + ((u[4] + u[5]) + (u[6] + u[7]));
    }
    uint32_t o;
    if (FMT == 2) o = pack2(y, __shfl_down_sync(0xffffffffu, y, 1));
    else o = __float_as_uint(FMT == 1 ? rbf(y) : y);
    o = enc(o);
    asm volatile("{.reg .pred p; setp.ne.u32 p, %2, 0; @p st.relaxed.gpu.global.u32 [%0], %1;}"
                 ::"l"(dst), "r"(o), "r"((uint32_t)(real && (FMT != 2 || !(lane & 1)))) : "memory");
  }
}

template <int NP, class F, class G>
__device__ __forceinline__ uint32_t add_partials(const uint32_t* p, uint32_t xw, bool real, F side, G after) {
  uint32_t a[NP], b[NP];
#pragma unroll
  for (int k = 0; k < NP; k++) a[k] = b[k] = 0u;
  int it = 0;
  bool pend, done = false;
  if (real) do {
#pragma unroll
    for (int k = 0; k < NP; k++)
      if (a[k] == 0u || b[k] == 0u) ldr64(a[k], b[k], p + k * 512);
    if (!done) done = side();
    pend = false;
#pragma unroll
    for (int k = 0; k < NP; k++) pend |= (a[k] == 0u || b[k] == 0u);
    if (!done) done = side();
    if (++it > SPIN_LIMIT) __trap();
  } while (__any_sync(0xffffffffu, pend) || !done);
  float y0 = 0.f, y1 = 0.f;
#pragma unroll
  for (int k = 0; k < NP; k++) { y0 += __uint_as_float(a[k]); y1 += __uint_as_float(b[k]); }
  asm volatile("" : "+f"(y0), "+f"(y1));
  after();
  return pack2(lo16(xw) + rbf(y0), hi16(xw) + rbf(y1));
}

__global__ void __launch_bounds__(NTHR, 1)
decode_kernel(const __grid_constant__ Maps maps, const uint32_t* __restrict__ x_in,
              const char* __restrict__ Kp, const char* __restrict__ Vp, uint32_t* __restrict__ out) {
  extern __shared__ __align__(1024) unsigned char smem[];
  const uint32_t sb = (uint32_t)__cvta_generic_to_shared(smem);
  const int tid = threadIdx.x, lane = tid & 31;
  const int warp = __shfl_sync(0xffffffffu, tid >> 5, 0);
  const int cta = blockIdx.x;
  const uint32_t t_start = __shfl_sync(0xffffffffu, (uint32_t)clock(), 0);
  const int head_lo = cta < 128 ? ((cta + 3 * (cta >> 3)) & 7) : 2 * (cta - 128), head_hi = cta < 128 ? head_lo : head_lo + 1;
  const int head = warp < 4 ? head_lo : head_hi;
  const int jw = cta < 128 ? (cta >> 3) * 8 + warp : 128 + (warp & 3);
  const uint32_t ring = sb + warp * WARP_BYTES;
  const uint32_t rbar = sb + SM_BAR + warp * 40;
  const uint32_t wbar = rbar + 24;
  const uint32_t wseg = ring + O_W;

  auto w_issue = [&](int half, const CUtensorMap* m, int col, int row) {
    if (lane == 0) {
      mbar_expect(wbar + half * 8, 2048);
      tma2d(wseg + half * 2048, m, col, row, wbar + half * 8, pol_evict_first());
    }
    __syncwarp();
  };
  auto issue_demote = [&](int sl, int t) {
    if (lane == 0) {
      uint64_t pn;
      asm volatile("createpolicy.fractional.L2::evict_normal.b64 %0, 1.0;" : "=l"(pn));
      const uint64_t pf = pol_evict_first();
      const int row = head * SK + t * 16;
      const uint32_t dst = ring + sl * SLOT_BYTES, b = rbar + sl * 8;
      mbar_expect(b, SLOT_BYTES);
      tma3d(dst, &maps.k, row, b, pn);
      asm volatile("cp.async.bulk.prefetch.L2.global.L2::cache_hint [%0], %1, %2;" ::"l"(Kp + (size_t)row * 256), "r"(4096), "l"(pf) : "memory");
      tma3d(dst + 4096, &maps.v, row, b, pn);
      asm volatile("cp.async.bulk.prefetch.L2.global.L2::cache_hint [%0], %1, %2;" ::"l"(Vp + (size_t)row * 256), "r"(4096), "l"(pf) : "memory");
    }
    __syncwarp();
  };
  auto issue = [&](int sl, int t, bool kp) {
    if (lane == 0) {
      const uint64_t pf = pol_evict_first();
      const int row = head * SK + t * 16;
      const uint32_t dst = ring + sl * SLOT_BYTES, b = rbar + sl * 8;
      mbar_expect(b, SLOT_BYTES);
      tma3d(dst, &maps.k, row, b, pf);
      if (kp) l2_prefetch(Kp + (size_t)row * 256, 4096);
      tma3d(dst + 4096, &maps.v, row, b, pf);
      if (kp) l2_prefetch(Vp + (size_t)row * 256, 4096);
    }
    __syncwarp();
  };
  auto stack_tile = [&](uint32_t r) -> int { return r == 5 ? 6 * WPH + (jw >> 1) : jw + (r == 6 ? 5 : (int)r) * WPH; };

  uint32_t xw = __ldg(x_in + tid);
  if (lane == 0) {
    if (sb & 1023) __trap();
#pragma unroll
    for (int i = 0; i < 5; i++) mbar_init(rbar + i * 8, 1);
    asm volatile("fence.mbarrier_init.release.cluster;" ::: "memory");
    fence_async();
  }
  if (cta < 128) { w_issue(0, &maps.wq, cta * 32, warp * 64); w_issue(1, &maps.wq, cta * 32, warp * 64 + 32); }
  if (tid == 0 && cta < 128 && (cta & 15) == 0) {
    g_s.ctr[0][cta >> 4][0] = 0;
    asm volatile("fence.acq_rel.gpu;" ::: "memory");
  }
  __syncwarp();
  issue_demote(2, jw);
  if (tid == 32) {
    asm volatile("prefetch.tensormap [%0];" ::"l"(&maps.wo) : "memory");
    asm volatile("prefetch.tensormap [%0];" ::"l"(&maps.wg) : "memory");
    asm volatile("prefetch.tensormap [%0];" ::"l"(&maps.wu) : "memory");
    asm volatile("prefetch.tensormap [%0];" ::"l"(&maps.wd) : "memory");
  }
  __syncwarp();

  uint32_t c0[48], c1[48], c2[48], c3[48];
#pragma unroll
  for (int i = 0; i < 48; i++) { c0[i] = 0; c1[i] = 0; c2[i] = 0; c3[i] = 0; }
  uint32_t exc = 0;

  uint32_t sst = 0;

  for (int layer = -1; layer < 2; layer++) {
    const bool live = layer >= 0;
    const int ly = live ? layer : 0;

    if (live) {
      Attn st;
#pragma unroll
      for (int i = 0; i < 4; i++) { st.o[i][0] = st.o[i][1] = st.o[i][2] = st.o[i][3] = 0.f; }
      st.m0 = st.m1 = -INFINITY; st.l0 = st.l1 = 0.f;
      const int ln = fresh_lane();
      const uint32_t koff = ((ln & 7) + ((ln >> 3) & 1) * 8) * 128 + (((ln >> 4) ^ (ln & 7)) << 4);
      const uint32_t voff = 4096 + (ln >> 4) * 2048 + (ln & 7) * 128 + ((((ln >> 3) & 1) ^ (ln & 7)) << 4);
      const uint32_t qaddr = sb + SM_Q + ((head - head_lo) * 4 + (ln & 3)) * Q_PITCH + (ln >> 3) * 16;
      const bool lowg = ln < 16;
      int nxt = jw - NSTAT * WPH;
      if (layer == 0) { sst = 7; nxt += WPH; }
      else sst = ((sst ^ 0x10) & 0x3ff0770) | 1;
      while (true) {
        int sl = -1;
        if ((sst & 2) && mbar_test(rbar + 8, (sst >> 5) & 1)) sl = 1;
        if (sst & 4) sl = 2;
        if ((sst & 1) && mbar_test(rbar, (sst >> 4) & 1)) sl = 0;
        sl = __shfl_sync(0xffffffffu, sl, 0);
        if (sl >= 0) {
          tile_smem(st, ring + sl * SLOT_BYTES + koff, ring + sl * SLOT_BYTES + voff, qaddr, lowg);
          __syncwarp();
          sst ^= 0x11u << sl;
          if (sl == 0) sst |= 0x2000;
          if (layer == 0) {
            if (sl != 0 || (sst & 0x8000)) {
              const int l_ = fresh_lane();
              const uint32_t r = (sst >> 8) & 7, img = ring + sl * SLOT_BYTES;
              uint32_t bases, cnt = (sst >> 21) & 31;
              if (!pack_prepare(img, l_, r, bases, exc, cnt)) bases |= 0x10000;
              sst = ((sst & ~(31u << 21) & ~0x8000u) | (cnt << 21)) + ((r == 4 && (warp & 1)) ? 0x200 : 0x100);
              if (l_ == EXC_CAP + (int)r) exc = bases;
              if (r == 0) pack_tile(c0, img, l_, bases);
              else if (r == 1) pack_tile(c1, img, l_, bases);
              else if (r == 2) pack_tile(c2, img, l_, bases);
              else if (r == 3) pack_tile(c3, img, l_, bases);
              else {
                const uint32_t pk = ring + (r == 4 ? O_C1 : r == 5 ? O_E : O_C0);
                pack_tile_smem(pk, pk + (r == 5 ? WARP_BYTES : 3072), img, l_, bases);
              }
              fence_async();
              __syncwarp();
              if (sl == 1 && (sst & 0x700) < 0x600) { issue(1, stack_tile((sst >> 8) & 7), false); sst |= 2; }
            }
          } else if (sl == 1 && ((sst >> 16) & 31)) {
            sst -= 1u << 16;
            uint32_t t;
            asm volatile("ld.shared.u16 %0, [%1];" : "=r"(t) : "r"(sb + SM_LIST + warp * (KCAP * 2) + ((sst >> 16) & 31) * 2) : "memory");
            issue(1, t, false); sst |= 2;
          }
        } else if (layer == 1 && (sst & 0x700) && !(sst & 2) && ((sst & 0x2000) || !(sst & 1))) {
          const int l_ = fresh_lane();
          const uint32_t r = ((sst >> 8) & 7) - 1, img = ring + SLOT_BYTES;
          sst = ((sst - ((r == 6 && (warp & 1)) ? 0x200 : 0x100)) | 2) & ~0x2000u;
          const uint32_t hdr = __shfl_sync(0xffffffffu, exc, EXC_CAP + r);
          if (hdr & 0x10000) {
            issue(1, stack_tile(r), false);
          } else {
            if (r == 0) unpack_tile(c0, img, l_, hdr);
            else if (r == 1) unpack_tile(c1, img, l_, hdr);
            else if (r == 2) unpack_tile(c2, img, l_, hdr);
            else if (r == 3) unpack_tile(c3, img, l_, hdr);
            else {
              const uint32_t pk = ring + (r == 4 ? O_C1 : r == 5 ? O_E : O_C0);
              unpack_tile_smem(pk, pk + (r == 5 ? WARP_BYTES : 3072), img, l_, hdr);
            }
            __syncwarp();
            if (l_ < (int)((sst >> 21) & 31) && ((exc >> 12) & 7) == r)
              asm volatile("st.shared.u16 [%0], %1;" ::"r"(img + (exc & 0xfffu) * 2), "r"(exc >> 16) : "memory");
            fence_async();
            __syncwarp();
            if (l_ == 0) mbar_expect(rbar + 8, 0);
          }
          __syncwarp();
        } else if (warp == 7 && (sst & 0x88) == 8) {
          sst = (sst | 0x80) & ~0x2000u;
          const int l_ = fresh_lane(), c_ = opaque(cta), y_ = opaque(ly);
          const uint4 z = make_uint4(0, 0, 0, 0);
          const int s_lo = c_ >> 3;
          uint4* po = reinterpret_cast<uint4*>(&g_s.PO[y_][head_lo][s_lo][0]);
          po[l_] = z; po[l_ + 32] = z;
          if (l_ < 2) reinterpret_cast<uint4*>(&g_s.ML[y_][head_lo][s_lo][0])[l_] = z;
          if (head_hi != head_lo) {
            po = reinterpret_cast<uint4*>(&g_s.PO[y_][head_hi][16][0]);
            po[l_] = z; po[l_ + 32] = z;
            if (l_ < 2) reinterpret_cast<uint4*>(&g_s.ML[y_][head_hi][16][0])[l_] = z;
          }
          if (c_ < 128) {
            (&g_s.Y1[y_][0][0])[c_ * 32 + l_] = 0;
            if (y_ == 0 && l_ < 16) g_s.QX[1][c_ * 16 + l_] = 0;
          }
          if (c_ < 112) { g_s.GU[y_][c_ * 32 + l_] = 0; (&g_s.Y2[y_][0][0])[c_ * 32 + l_] = 0; }
          if (c_ < 8 && y_ == 0 && l_ == 0) g_s.ctr[1][c_][0] = 0;
          __syncwarp();
          if (l_ == 0) {
            asm volatile("fence.acq_rel.gpu;" ::: "memory");
            const uint32_t old = atomicAdd(&g_s.cnt[y_][0], 1u);
            sts32(sb + SM_STAT + 64, (old / NCTA + 1) * NCTA);
          }
          __syncwarp();
        } else if ((sst & 7) == 0) {
          break;
        } else if ((sst & 0x3080) == 0x2080) {
          uint32_t target, c;
          asm volatile("ld.shared.u32 %0, [%1];" : "=r"(target) : "r"(sb + SM_STAT + 64) : "memory");
          asm volatile("ld.acquire.gpu.global.u32 %0, [%1];" : "=r"(c) : "l"(&g_s.cnt[opaque(ly)][0]) : "memory");
          sst &= ~0x2000u;
          if (__all_sync(0xffffffffu, (int)(c - target) >= 0)) sst |= 0x1000;
        } else if (__any_sync(0xffffffffu, (uint32_t)clock() - t_start > 0xc0000000u)) {
          __trap();
        }
        if (!(sst & 0x801)) {
          if (layer == 0 && (sst & 0x700) == 0x600) {
            issue(0, stack_tile(6), false); sst |= 0x8001;
          } else {
            const int d = __shfl_sync(0xffffffffu, nxt, 8) + NSTAT * WPH;
            const int nd = layer == 0 ? N_ALL : N_DYN;
            if (d >= nd - RESET_X) sst |= 8;
            if (d < nd) {
              const bool kp = d >= N_DYN;
              issue(0, T_DYN + d, kp); sst |= 1;
              if (kp) {
                if (lane == 0)
                  asm volatile("st.shared.u16 [%0], %1;" ::"r"(sb + SM_LIST + warp * (KCAP * 2) + ((sst >> 16) & 31) * 2), "r"(T_DYN + d) : "memory");
                sst += 1u << 16;
              }
              const bool full = (layer == 0 && ((sst >> 16) & 31) == KCAP) || ((warp & 3) == 0 && d >= nd - STOP_X), stat = d < (NSTAT - 1) * WPH;
              nxt = full ? 1 << 20 : d - (NSTAT - 1) * WPH;
              if (layer == 0 && !stat && d < NSTAT * WPH) {
                uint32_t qw;
                asm volatile("ld.acquire.gpu.global.u32 %0, [%1];" : "=r"(qw) : "l"(&g_s.QX[0][head * 256]) : "memory");
              }
              asm volatile("{.reg .pred p; setp.ne.u32 p, %2, 0; @p atom.global.relaxed.gpu.inc.u32 %0, [%1], 0x7fffffff;}"
                           : "+r"(nxt) : "l"(&g_s.ctr[layer][head][0]), "r"((uint32_t)(lane == 8 && !full && !stat)) : "memory");
              __syncwarp();
            } else if (layer == 1) {
              sst |= 0x800;
            } else if ((sst & 0x700) == 0x700) {
              issue(0, T_LAST + jw, false); sst |= 0x801;
            }
          }
        }
      }
      int rank = __shfl_sync(0xffffffffu, nxt, 8) + NSTAT * WPH - (layer == 0 ? N_ALL : N_DYN);

      {
#pragma unroll
        for (int o = 4; o <= 16; o <<= 1) {
          st.l0 += __shfl_xor_sync(0xffffffffu, st.l0, o);
          st.l1 += __shfl_xor_sync(0xffffffffu, st.l1, o);
        }
        const int g = lane >> 2, t = lane & 3;
        const uint32_t a = ring + O_P + ((t & 1) * 128 + (t >> 1) * 64) * 4;
#pragma unroll
        for (int mt = 0; mt < 4; mt++) {
          sts32(a + ((16 * mt + g) ^ (8 * t)) * 4, pack2(st.o[mt][0], st.o[mt][1]));
          sts32(a + ((16 * mt + 8 + g) ^ (8 * t)) * 4, pack2(st.o[mt][2], st.o[mt][3]));
        }
        if (lane < 2)
          sts128(sb + SM_ML + warp * 32 + lane * 16, __float_as_uint(st.m0), __float_as_uint(st.l0),
                 __float_as_uint(st.m1), __float_as_uint(st.l1));
      }
      {
        const int hp = tid >> 7, d = tid & 127, odd = tid & 1, hq = 2 * hp + odd;
        uint32_t* ppo = pin(&g_s.PO[ly][head_lo][cta >> 3][hq * 64 + (d >> 1)]);
        uint32_t* pml = pin(&g_s.ML[ly][head_lo][cta >> 3][2 * hq]);
        uint32_t am = sb + SM_ML + hp * 16 + odd * 8;
        uint32_t ap = sb + O_P + (hp * 128 + ((d & ~1) ^ (8 * (hp + 2 * (d >> 6))))) * 4;
        uint32_t sel = odd ? 0x7632 : 0x5410;
        asm volatile("" : "+r"(am), "+r"(ap), "+r"(sel));
        if (cta < 128) {
          if (rank > 100000) rank = STOP_R;
          if (rank < WO_R0) {
            const uint32_t c0_ = clock();
            while (__any_sync(0xffffffffu, (uint32_t)clock() - c0_ < (uint32_t)((WO_R0 - rank) * WO_K))) {}
          }
          w_issue(0, &maps.wo, (cta & 15) * 32, (cta >> 4) * 512 + warp * 64);
        }
        __syncthreads();
        float mw[8], lw[8];
        uint32_t u[8];
#pragma unroll
        for (int w = 0; w < 8; w++) ldsf2(mw[w], lw[w], am + w * 32);
#pragma unroll
        for (int w = 0; w < 8; w++) {
          uint32_t x0, x1;
          asm volatile("ld.shared.v2.u32 {%0,%1}, [%2];" : "=r"(x0), "=r"(x1) : "r"(ap + w * WARP_BYTES) : "memory");
          u[w] = __byte_perm(x0, x1, sel);
        }
        const bool split = head_hi != head_lo;
        float Ma = fmaxf(fmaxf(mw[0], mw[1]), fmaxf(mw[2], mw[3]));
        float Mb = fmaxf(fmaxf(mw[4], mw[5]), fmaxf(mw[6], mw[7]));
        if (!split) Ma = Mb = fmaxf(Ma, Mb);
        float La = 0.f, a0 = 0.f, a1 = 0.f, Lb = 0.f, b0 = 0.f, b1 = 0.f;
#pragma unroll
        for (int w = 0; w < 4; w++) {
          const float ea = ex2(mw[w] - Ma), eb = ex2(mw[w + 4] - Mb);
          La = fmaf(lw[w], ea, La); a0 = fmaf(lo16(u[w]), ea, a0); a1 = fmaf(hi16(u[w]), ea, a1);
          Lb = fmaf(lw[w + 4], eb, Lb); b0 = fmaf(lo16(u[w + 4]), eb, b0); b1 = fmaf(hi16(u[w + 4]), eb, b1);
        }
        if (!split) { La += Lb; a0 += b0; a1 += b1; }
        if (d < 2) str64(pml, enc(__float_as_uint(Ma)), enc(__float_as_uint(La)));
        const float ia = rcp(La);
        str32(ppo, enc(pack2(a0 * ia, a1 * ia)));
        if (split) {
          if (d < 2) str64(pml + 17 * 8, enc(__float_as_uint(Mb)), enc(__float_as_uint(Lb)));
          const float ib = rcp(Lb);
          str32(ppo + 17 * 256, enc(pack2(b0 * ib, b1 * ib)));
        }
      }
      if (cta < 128) w_issue(1, &maps.wo, (cta & 15) * 32, (cta >> 4) * 512 + warp * 64 + 32);
      if (tid == 255 && !(sst & 0x1000)) {
        uint32_t target, c;
        asm volatile("ld.shared.u32 %0, [%1];" : "=r"(target) : "r"(sb + SM_STAT + 64) : "memory");
        int it = 0;
        do {
          asm volatile("ld.acquire.gpu.global.u32 %0, [%1];" : "=r"(c) : "l"(&g_s.cnt[ly][0]) : "memory");
          if (++it > SPIN_LIMIT) __trap();
        } while ((int)(c - target) < 0);
      }
      __syncwarp();
      __syncthreads();
    }

    if (cta < 128) {
      uint32_t A[32];
      if (live) {
#pragma unroll 1
        for (int real = 0; real < 2; real++) {
#pragma unroll
          for (int i = 0; i < 16; i++) A[i] = 0u;
          const int rb = cta >> 4;
          const uint32_t* pp = pin(&g_s.PO[ly][rb][0][tid]);
          const uint32_t* pm = pin(&g_s.ML[ly][rb][lane < 17 ? lane : 0][2 * (warp >> 1)]);
          uint32_t v[17], um = 0u, ul = 0u;
#pragma unroll
          for (int s = 0; s < 17; s++) v[s] = 0u;
          int it = 0;
          bool pend, done = false;
          if (real) {
            do {
              if (um == 0u || ul == 0u) ldr64(um, ul, pm);
#pragma unroll
              for (int s = 0; s < 17; s++)
                if (v[s] == 0u) v[s] = ldr32(pp + s * 256);
              if (!done && __all_sync(0xffffffffu, mbar_test(wbar, 1))) {
                w_frags<0>(A, wseg, lane);
                __syncwarp();
                if (cta < 112) w_issue(0, cta < 56 ? &maps.wg : &maps.wu, (cta < 56 ? cta : cta - 56) * 32, warp * 64);
                else if (layer == 0) w_issue(0, &maps.wq, cta * 32, warp * 64);
                done = true;
              }
              pend = (um == 0u || ul == 0u);
#pragma unroll
              for (int s = 0; s < 17; s++) pend |= (v[s] == 0u);
              if (++it > SPIN_LIMIT) __trap();
            } while (__any_sync(0xffffffffu, pend) || !done);
          }
          const float ms = __uint_as_float(um);
          int mi = __float_as_int(ms);
          mi = __reduce_max_sync(0xffffffffu, mi ^ ((mi >> 31) & 0x7fffffff));
          const float M = __int_as_float(mi ^ ((mi >> 31) & 0x7fffffff));
          const float e = lane < 17 ? __uint_as_float(ul) * ex2(ms - M) : 0.f;
          float L = 0.f, o0 = 0.f, o1 = 0.f, Lb = 0.f, p0 = 0.f, p1 = 0.f;
#pragma unroll
          for (int s = 0; s < 17; s++) {
            const float es = __shfl_sync(0xffffffffu, e, s);
            if (s & 1) { Lb += es; p0 = fmaf(es, lo16(v[s]), p0); p1 = fmaf(es, hi16(v[s]), p1); }
            else { L += es; o0 = fmaf(es, lo16(v[s]), o0); o1 = fmaf(es, hi16(v[s]), o1); }
          }
          o0 += p0; o1 += p1;
          asm volatile("" : "+f"(o0), "+f"(o1));
          if (real) mbar_wait(wbar + 8, cta < 112 ? layer ^ 1 : 1);
          w_frags<1>(A, wseg + 2048, lane);
          const float inv = rcp(L + Lb);
          gemv_regs<4, false, 0>(A, sb, warp, lane, pack2(o0 * inv, o1 * inv), &g_s.Y1[ly][0][0] + cta * 32 + lane, real);
          if (real) {
            if (cta < 112) w_issue(1, cta < 56 ? &maps.wg : &maps.wu, (cta < 56 ? cta : cta - 56) * 32, warp * 64 + 32);
            else if (layer == 0) w_issue(1, &maps.wq, cta * 32, warp * 64 + 32);
          }
          __syncthreads();
        }
#pragma unroll 1
        for (int real = 0; real < 2; real++) {
#pragma unroll
          for (int i = 0; i < 16; i++) A[i] = 0u;
          const uint32_t xn = add_partials<8>(pin(&g_s.Y1[ly][0][2 * tid]), xw, real, [&]() {
            if (cta >= 112) return true;
            if (!__all_sync(0xffffffffu, mbar_test(wbar, 0))) return false;
            w_frags<0>(A, wseg, lane);
            __syncwarp();
            w_issue(0, &maps.wd, (cta & 15) * 32, (cta >> 4) * 256 + warp * 32);
            return true;
          }, [&]() { if (real && cta < 112) mbar_wait(wbar + 8, layer); w_frags<1>(A, wseg + 2048, lane); });
          if (real) { xw = xn; }
          if (cta < 112) {
            gemv_regs<4, true, 1>(A, sb, warp, lane, xn, &g_s.GU[ly][cta * 32 + lane], real);
            if (real) {
              if (layer == 0) {
                w_issue(1, &maps.wq, cta * 32, warp * 64 + 32);
              }
            }
            __syncthreads();
          }
        }
        if (cta < 112) {
#pragma unroll 1
          for (int real = 0; real < 2; real++) {
#pragma unroll
            for (int i = 0; i < 16; i++) A[i] = 0u;
            const uint32_t* pg = pin(&g_s.GU[ly][(lane >> 4) * FF + (cta >> 4) * 256 + warp * 32 + (lane & 15) * 2]);
            uint32_t a = 0u, b = 0u;
            int it = 0;
            bool done = false;
            if (real) {
              do {
                if (a == 0u || b == 0u) ldr64(a, b, pg);
                if (!done && __all_sync(0xffffffffu, mbar_test(wbar, 1))) {
                  w_frags<0>(A, wseg, lane);
                  __syncwarp();
                  if (layer == 0) { w_issue(0, &maps.wq, cta * 32, warp * 64); }
                  done = true;
                }
                if (++it > SPIN_LIMIT) __trap();
              } while (__any_sync(0xffffffffu, a == 0u || b == 0u) || !done);
            }
            const float a0 = __uint_as_float(a), a1 = __uint_as_float(b);
            const float c0_ = __shfl_xor_sync(0xffffffffu, a0, 16), c1_ = __shfl_xor_sync(0xffffffffu, a1, 16);
            const float g0 = lane < 16 ? a0 : c0_, g1 = lane < 16 ? a1 : c1_;
            const float u0 = lane < 16 ? c0_ : a0, u1 = lane < 16 ? c1_ : a1;
            const uint32_t hw = pack2((g0 > 0.f ? g0 : g0 * 0.f) * u0, (g1 > 0.f ? g1 : g1 * 0.f) * u1);
            gemv_regs<2, false, 0>(A, sb, warp, lane, hw, &g_s.Y2[ly][0][0] + cta * 32 + lane, real);
            __syncthreads();
          }
        }
        if (layer == 1 && cta != 127) break;
        if (layer == 0 && warp == 4) {
          if (lane < 16) g_s.QX[0][cta * 16 + lane] = 0;
          __syncwarp();
        }
      }
#pragma unroll 1
      for (int real = live ? 0 : 1; real < 2; real++) {
#pragma unroll
        for (int i = 0; i < 16; i++) A[i] = 0u;
        if (!live) {
          mbar_wait(wbar, 0); mbar_wait(wbar + 8, 0);
          w_frags<0>(A, wseg, lane);
        }
        const uint32_t xn = add_partials<7>(pin(&g_s.Y2[ly][0][2 * tid]), xw, real && live, [&]() {
          if (layer == 1) return true;
          if (!__all_sync(0xffffffffu, mbar_test(wbar, 0) && mbar_test(wbar + 8, cta < 112 ? 1 : 0))) return false;
          w_frags<0>(A, wseg, lane);
          return true;
        }, [&]() { w_frags<1>(A, wseg + 2048, lane); });
        if (real && live) {
          xw = xn;
          if (layer == 1) { out[tid] = xn; return; }
        }
        gemv_regs<4, true, 2>(A, sb, warp, lane, xw, &g_s.QX[(layer + 1) & 1][cta * 16 + (lane >> 1)], real);
        if (!real) __syncthreads();
      }
    } else if (layer == 1) {
      break;
    }
    if (!live) {
      mbar_wait(rbar + 16, 0);
      issue_demote(1, jw + WPH);
    }
    __syncthreads();
    {
      const uint32_t* pq = &g_s.QX[layer + 1][head_lo * 256 + tid];
      uint32_t qv0 = 0u, qv1 = head_hi != head_lo ? 0u : 1u;
      int it = 0;
      do {
        if (qv0 == 0u) qv0 = ldr32(pq);
        if (qv1 == 0u) qv1 = ldr32(pq + 256);
        if (++it > SPIN_LIMIT) __trap();
      } while (__any_sync(0xffffffffu, qv0 == 0u || qv1 == 0u));
      if (!live) issue_demote(0, T_DYN + jw);
      sts32(sb + SM_Q + (tid >> 6) * Q_PITCH + (tid & 63) * 4, qv0);
      sts32(sb + SM_Q + (4 + (tid >> 6)) * Q_PITCH + (tid & 63) * 4, qv1);
    }
    __syncthreads();
  }
}

typedef CUresult (*EncodeFn)(CUtensorMap*, CUtensorMapDataType, cuuint32_t, void*, const cuuint64_t*,
                             const cuuint64_t*, const cuuint32_t*, const cuuint32_t*, CUtensorMapInterleave,
                             CUtensorMapSwizzle, CUtensorMapL2promotion, CUtensorMapFloatOOBfill);

void make_kv_map(EncodeFn enc, CUtensorMap* m, void* p) {
  cuuint64_t dims[3] = {64, (cuuint64_t)8 * SK, 2};
  cuuint64_t strides[2] = {256, 128};
  cuuint32_t box[3] = {64, 16, 2}, es[3] = {1, 1, 1};
  enc(m, CU_TENSOR_MAP_DATA_TYPE_BFLOAT16, 3, p, dims, strides, box, es, CU_TENSOR_MAP_INTERLEAVE_NONE,
      CU_TENSOR_MAP_SWIZZLE_128B, CU_TENSOR_MAP_L2_PROMOTION_NONE, CU_TENSOR_MAP_FLOAT_OOB_FILL_NONE);
}
void make_w_map(EncodeFn enc, CUtensorMap* m, void* p, int rows, int cols) {
  cuuint64_t dims[2] = {(cuuint64_t)cols, (cuuint64_t)rows};
  cuuint64_t strides[1] = {(cuuint64_t)cols * 2};
  cuuint32_t box[2] = {32, 32}, es[2] = {1, 1};
  enc(m, CU_TENSOR_MAP_DATA_TYPE_BFLOAT16, 2, p, dims, strides, box, es, CU_TENSOR_MAP_INTERLEAVE_NONE,
      CU_TENSOR_MAP_SWIZZLE_64B, CU_TENSOR_MAP_L2_PROMOTION_NONE, CU_TENSOR_MAP_FLOAT_OOB_FILL_NONE);
}

}

extern "C" void kernel_launch(void* const* d_in, const int* in_sizes, int n_in, void* d_out, int out_size) {
  (void)in_sizes; (void)n_in; (void)out_size;
  void* fn = nullptr;
  cudaDriverEntryPointQueryResult qr;
  cudaGetDriverEntryPoint("cuTensorMapEncodeTiled", &fn, cudaEnableDefault, &qr);
  EncodeFn enc = (EncodeFn)fn;
  Maps maps;
  make_kv_map(enc, &maps.k, d_in[1]);
  make_kv_map(enc, &maps.v, d_in[2]);
  make_w_map(enc, &maps.wq, d_in[3], DM, 4096);
  make_w_map(enc, &maps.wo, d_in[4], 4096, DM);
  make_w_map(enc, &maps.wg, d_in[6], DM, FF);
  make_w_map(enc, &maps.wu, d_in[7], DM, FF);
  make_w_map(enc, &maps.wd, d_in[8], FF, DM);
  cudaFuncSetAttribute(decode_kernel, cudaFuncAttributeMaxDynamicSharedMemorySize, SM_TOTAL);
  decode_kernel<<<NCTA, NTHR, SM_TOTAL, cudaStreamPerThread>>>(
      maps, (const uint32_t*)d_in[0], (const char*)d_in[1], (const char*)d_in[2], (uint32_t*)d_out);
}
```

```cpp
#include <cuda_runtime.h>
#include <cuda_bf16.h>
#include <cuda.h>
#include <stdint.h>

namespace {

constexpr int NCTA = 132, NWARP = 8, NTHR = 256;
constexpr int DM = 512, SK = 65536, FF = 1792;
constexpr int WPH = NCTA;
constexpr int SLOT_BYTES = 8192;
constexpr int KEEP_H = 760;
constexpr int RESET_X = 400;
constexpr int STOP_X = 700;
constexpr int WO_K = 25;
constexpr int WO_R0 = 60;
constexpr int STOP_R = -80;
constexpr int NSTAT = 4;
constexpr int T_DYN = 6 * 132 + 66;
constexpr int T_LAST = 4096 - 132;
constexpr int N_ALL = T_LAST - T_DYN;
constexpr int N_DYN = N_ALL - KEEP_H;
constexpr int KCAP = 12;
static_assert(KCAP * 99 > KEEP_H, "the warps that stream to the end must be able to take all kept tiles");
static_assert(N_DYN - STOP_X >= NSTAT * 132, "");

constexpr int WARP_BYTES = 28672;
constexpr int O_W = 8192, O_C0 = 12288, O_C1 = 18432, O_E = 24576, O_P = 27648;
constexpr int SM_BAR = NWARP * WARP_BYTES;
constexpr int SM_STAT = SM_BAR + 320;
constexpr int SM_Q = SM_STAT + 128;
constexpr int Q_PITCH = 272;
constexpr int SM_LIST = SM_Q + 2 * 4 * Q_PITCH;
constexpr int SM_ML = SM_LIST + NWARP * KCAP * 2;
constexpr int SM_TOTAL = SM_ML + NWARP * 32;
static_assert(SM_TOTAL <= 232448, "");

struct Scratch {
  uint32_t QX[2][2048];
  uint32_t PO[2][8][17][256];
  uint32_t ML[2][8][17][8];
  uint32_t Y1[2][8][512];
  uint32_t GU[2][2 * FF];
  uint32_t Y2[2][7][512];
  uint32_t cnt[2][32];
  uint32_t ctr[2][8][32];
};
__device__ __align__(1024) Scratch g_s;

struct Maps { CUtensorMap k, v, wq, wo, wg, wu, wd; };

constexpr int SPIN_LIMIT = 1 << 22;

__device__ __forceinline__ void mbar_init(uint32_t bar, int cnt) {
  asm volatile("mbarrier.init.shared::cta.b64 [%0], %1;" ::"r"(bar), "r"(cnt) : "memory");
}
__device__ __forceinline__ void mbar_expect(uint32_t bar, uint32_t bytes) {
  asm volatile("mbarrier.arrive.expect_tx.shared::cta.b64 _, [%0], %1;" ::"r"(bar), "r"(bytes) : "memory");
}
__device__ __forceinline__ void mbar_wait(uint32_t bar, uint32_t parity) {
  uint32_t ok;
  int it = 0;
  do {
    asm volatile("{.reg .pred p; mbarrier.try_wait.parity.shared::cta.b64 p, [%1], %2; selp.u32 %0,1,0,p;}"
                 : "=r"(ok) : "r"(bar), "r"(parity) : "memory");
    if (++it > SPIN_LIMIT) __trap();
  } while (!__all_sync(0xffffffffu, ok));
}
__device__ __forceinline__ bool mbar_test(uint32_t bar, uint32_t parity) {
  uint32_t ok;
  asm volatile("{.reg .pred p; mbarrier.test_wait.parity.shared::cta.b64 p, [%1], %2; selp.u32 %0,1,0,p;}"
               : "=r"(ok) : "r"(bar), "r"(parity) : "memory");
  return ok != 0;
}
__device__ __forceinline__ int fresh_lane() { int l; asm volatile("mov.u32 %0, %laneid;" : "=r"(l)); return l; }
template <class T> __device__ __forceinline__ T* pin(T* p) { asm volatile("" : "+l"(p)); return p; }
__device__ __forceinline__ int opaque(int x) { asm volatile("" : "+r"(x)); return x; }
__device__ __forceinline__ void tma3d(uint32_t dst, const CUtensorMap* m, int row, uint32_t bar, uint64_t pol) {
  asm volatile("cp.async.bulk.tensor.3d.shared::cluster.global.mbarrier::complete_tx::bytes.L2::cache_hint"
               " [%0], [%1, {%3, %4, %3}], [%2], %5;"
               ::"r"(dst), "l"(m), "r"(bar), "r"(0), "r"(row), "l"(pol) : "memory");
}
__device__ __forceinline__ void tma2d(uint32_t dst, const CUtensorMap* m, int col, int row, uint32_t bar, uint64_t pol) {
  asm volatile("cp.async.bulk.tensor.2d.shared::cluster.global.mbarrier::complete_tx::bytes.L2::cache_hint"
               " [%0], [%1, {%3, %4}], [%2], %5;"
               ::"r"(dst), "l"(m), "r"(bar), "r"(col), "r"(row), "l"(pol) : "memory");
}
__device__ __forceinline__ void l2_prefetch(const void* p, uint32_t bytes) {
  asm volatile("cp.async.bulk.prefetch.L2.global [%0], %1;" ::"l"(p), "r"(bytes) : "memory");
}
__device__ __forceinline__ uint64_t pol_evict_first() {
  uint64_t p;
  asm volatile("createpolicy.fractional.L2::evict_first.b64 %0, 1.0;" : "=l"(p));
  return p;
}
__device__ __forceinline__ void ldsm4(uint32_t& a, uint32_t& b, uint32_t& c, uint32_t& d, uint32_t addr) {
  asm volatile("ldmatrix.sync.aligned.m8n8.x4.shared.b16 {%0,%1,%2,%3}, [%4];"
               : "=r"(a), "=r"(b), "=r"(c), "=r"(d) : "r"(addr) : "memory");
}
__device__ __forceinline__ void ldsm4t(uint32_t& a, uint32_t& b, uint32_t& c, uint32_t& d, uint32_t addr) {
  asm volatile("ldmatrix.sync.aligned.m8n8.x4.trans.shared.b16 {%0,%1,%2,%3}, [%4];"
               : "=r"(a), "=r"(b), "=r"(c), "=r"(d) : "r"(addr) : "memory");
}
__device__ __forceinline__ void mma(float (&c)[4], uint32_t a0, uint32_t a1, uint32_t a2, uint32_t a3,
                                    uint32_t b0, uint32_t b1) {
  asm volatile("mma.sync.aligned.m16n8k16.row.col.f32.bf16.bf16.f32 {%0,%1,%2,%3}, {%4,%5,%6,%7}, {%8,%9}, {%0,%1,%2,%3};"
               : "+f"(c[0]), "+f"(c[1]), "+f"(c[2]), "+f"(c[3])
               : "r"(a0), "r"(a1), "r"(a2), "r"(a3), "r"(b0), "r"(b1));
}
__device__ __forceinline__ uint32_t movm(uint32_t a) {
  uint32_t d;
  asm volatile("movmatrix.sync.aligned.m8n8.trans.b16 %0, %1;" : "=r"(d) : "r"(a));
  return d;
}
__device__ __forceinline__ uint32_t pack2(float lo, float hi) {
  uint32_t d;
  asm("cvt.rn.bf16x2.f32 %0, %1, %2;" : "=r"(d) : "f"(hi), "f"(lo));
  return d;
}
__device__ __forceinline__ float lo16(uint32_t w) { return __uint_as_float(w << 16); }
__device__ __forceinline__ float hi16(uint32_t w) { return __uint_as_float(w & 0xffff0000u); }
__device__ __forceinline__ float rbf(float x) { return lo16(pack2(x, 0.f)); }
__device__ __forceinline__ float ex2(float x) {
  float y;
  asm("ex2.approx.ftz.f32 %0, %1;" : "=f"(y) : "f"(x));
  return y;
}
__device__ __forceinline__ float rcp(float x) {
  float y;
  asm("rcp.approx.ftz.f32 %0, %1;" : "=f"(y) : "f"(x));
  return y;
}
__device__ __forceinline__ uint32_t enc(uint32_t w) { return w ? w : 0x80000000u; }
__device__ __forceinline__ uint32_t ldr32(const uint32_t* p) {
  uint32_t v;
  asm volatile("ld.relaxed.gpu.global.u32 %0, [%1];" : "=r"(v) : "l"(p) : "memory");
  return v;
}
__device__ __forceinline__ void ldr64(uint32_t& a, uint32_t& b, const uint32_t* p) {
  asm volatile("ld.relaxed.gpu.global.v2.u32 {%0,%1}, [%2];" : "=r"(a), "=r"(b) : "l"(p) : "memory");
}
__device__ __forceinline__ void str32(uint32_t* p, uint32_t v) {
  asm volatile("st.relaxed.gpu.global.u32 [%0], %1;" ::"l"(p), "r"(v) : "memory");
}
__device__ __forceinline__ void str64(uint32_t* p, uint32_t a, uint32_t b) {
  asm volatile("st.relaxed.gpu.global.v2.u32 [%0], {%1,%2};" ::"l"(p), "r"(a), "r"(b) : "memory");
}
__device__ __forceinline__ void sts32(uint32_t addr, uint32_t v) {
  asm volatile("st.shared.u32 [%0], %1;" ::"r"(addr), "r"(v) : "memory");
}
__device__ __forceinline__ void stsf(uint32_t addr, float v) {
  asm volatile("st.shared.f32 [%0], %1;" ::"r"(addr), "f"(v) : "memory");
}
__device__ __forceinline__ void stsf2(uint32_t addr, float a, float b) {
  asm volatile("st.shared.v2.f32 [%0], {%1,%2};" ::"r"(addr), "f"(a), "f"(b) : "memory");
}
__device__ __forceinline__ float ldsf(uint32_t addr) {
  float v;
  asm volatile("ld.shared.f32 %0, [%1];" : "=f"(v) : "r"(addr) : "memory");
  return v;
}
__device__ __forceinline__ void ldsf2(float& a, float& b, uint32_t addr) {
  asm volatile("ld.shared.v2.f32 {%0,%1}, [%2];" : "=f"(a), "=f"(b) : "r"(addr) : "memory");
}
__device__ __forceinline__ void fence_async() { asm volatile("fence.proxy.async.shared::cta;" ::: "memory"); }

constexpr float SCALE_C = 0.08838834764831845f * 1.4426950408889634f;

struct Attn {
  float o[4][4];
  float m0, m1, l0, l1;
};

__device__ __forceinline__ void softmax_step(Attn& st, const float (&s)[4], uint32_t& r0, uint32_t& r1) {
  float t0 = fmaxf(s[0], s[2]), t1 = fmaxf(s[1], s[3]);
#pragma unroll
  for (int o = 4; o <= 16; o <<= 1) {
    t0 = fmaxf(t0, __shfl_xor_sync(0xffffffffu, t0, o));
    t1 = fmaxf(t1, __shfl_xor_sync(0xffffffffu, t1, o));
  }
  float n0 = fmaxf(st.m0, t0 * SCALE_C), n1 = fmaxf(st.m1, t1 * SCALE_C);
  float a0 = ex2(st.m0 - n0), a1 = ex2(st.m1 - n1);
  st.m0 = n0; st.m1 = n1;
  float p0 = ex2(fmaf(s[0], SCALE_C, -n0)), p1 = ex2(fmaf(s[1], SCALE_C, -n1));
  float p2 = ex2(fmaf(s[2], SCALE_C, -n0)), p3 = ex2(fmaf(s[3], SCALE_C, -n1));
  r0 = movm(pack2(p0, p1));
  r1 = movm(pack2(p2, p3));
  st.l0 = fmaf(st.l0, a0, p0 + p2);
  st.l1 = fmaf(st.l1, a1, p1 + p3);
#pragma unroll
  for (int i = 0; i < 4; i++) {
    st.o[i][0] *= a0; st.o[i][1] *= a1; st.o[i][2] *= a0; st.o[i][3] *= a1;
  }
}

__device__ __forceinline__ void tile_smem(Attn& st, uint32_t kaddr, uint32_t vaddr, uint32_t qaddr, bool lowg) {
  float s[4] = {0.f, 0.f, 0.f, 0.f}, s2[4] = {0.f, 0.f, 0.f, 0.f};
#pragma unroll
  for (int j = 0; j < 4; j++) {
    uint32_t q0, q1, q2, q3, a0, a1, a2, a3, c0, c1, c2, c3;
    ldsm4(q0, q1, q2, q3, qaddr + j * 64);
    ldsm4(a0, a1, a2, a3, (kaddr ^ (((2 * j) & 3) << 5)) + (j >> 1) * 2048);
    ldsm4(c0, c1, c2, c3, (kaddr ^ (((2 * j + 1) & 3) << 5)) + (j >> 1) * 2048);
    mma(s, a0, a1, a2, a3, q0, q1);
    mma(s2, c0, c1, c2, c3, q2, q3);
  }
#pragma unroll
  for (int i = 0; i < 4; i++) s[i] += s2[i];
  uint32_t r0, r1;
  softmax_step(st, s, r0, r1);
#pragma unroll
  for (int kg = 0; kg < 2; kg++) {
    uint32_t r = kg ? r1 : r0;
    uint32_t b0 = lowg ? r : 0u, b1 = lowg ? 0u : r;
#pragma unroll
    for (int mt = 0; mt < 4; mt++) {
      uint32_t a0, a1, a2, a3;
      ldsm4t(a0, a1, a2, a3, (vaddr ^ (mt << 5)) + kg * 1024);
      mma(st.o[mt], a0, a1, a2, a3, b0, b1);
    }
  }
}

__device__ __forceinline__ void lds128(uint32_t& a, uint32_t& b, uint32_t& c, uint32_t& d, uint32_t addr) {
  asm volatile("ld.shared.v4.u32 {%0,%1,%2,%3}, [%4];" : "=r"(a), "=r"(b), "=r"(c), "=r"(d) : "r"(addr) : "memory");
}
__device__ __forceinline__ void sts128(uint32_t addr, uint32_t a, uint32_t b, uint32_t c, uint32_t d) {
  asm volatile("st.shared.v4.u32 [%0], {%1,%2,%3,%4};" ::"r"(addr), "r"(a), "r"(b), "r"(c), "r"(d) : "memory");
}

constexpr uint32_t PK_M = 0x78007800u, PK_S = 0x80008000u;
constexpr int EXC_CAP = 25;

__device__ __forceinline__ uint32_t lds32(uint32_t addr) {
  uint32_t v;
  asm volatile("ld.shared.u32 %0, [%1];" : "=r"(v) : "r"(addr) : "memory");
  return v;
}

__device__ __forceinline__ bool pack_prepare(uint32_t img, int lane, int r, uint32_t& bases, uint32_t& exc, uint32_t& cnt) {
  bool ok = true;
  bases = 0;
  uint32_t c = cnt;
#pragma unroll 1
  for (int h = 0; h < 2; h++) {
    const uint32_t base = img + h * 4096 + lane * 16;
    uint32_t mx = 0u, mn = 0xffffffffu;
#pragma unroll
    for (int i = 0; i < 8; i++) {
      uint32_t w0, w1, w2, w3;
      lds128(w0, w1, w2, w3, base + i * 512);
      w0 &= ~PK_S; w1 &= ~PK_S; w2 &= ~PK_S; w3 &= ~PK_S;
      mx = __vimax3_u16x2(mx, w0, w1); mx = __vimax3_u16x2(mx, w2, w3);
      mn = __viaddmin_u16x2(w0, 0xffffffffu, mn); mn = __viaddmin_u16x2(w1, 0xffffffffu, mn);
      mn = __viaddmin_u16x2(w2, 0xffffffffu, mn); mn = __viaddmin_u16x2(w3, 0xffffffffu, mn);
    }
    const uint32_t e = __reduce_max_sync(0xffffffffu, max(mx & 0xffffu, mx >> 16)) >> 7;
    const uint32_t B = e > 15u ? e - 15u : 0u, thr = B << 7;
    bases |= B << (8 * h);
    uint32_t todo = __ballot_sync(0xffffffffu, min(mn & 0xffffu, mn >> 16) < thr);
    if (__popc(todo) > 8) ok = false;
    while (todo && ok) {
      const int src = __ffs(todo) - 1;
      todo &= todo - 1;
      const uint32_t off = h * 4096 + src * 16 + (lane >> 2) * 512 + (lane & 3) * 4;
      const uint32_t w = lds32(img + off);
#pragma unroll 1
      for (int j = 0; j < 2; j++) {
        const uint32_t v = j ? w >> 16 : w & 0xffffu;
        uint32_t m = __ballot_sync(0xffffffffu, (v & 0x7fffu) - 1u < thr);
        if (c + __popc(m) > EXC_CAP) { ok = false; break; }
        while (m) {
          const uint32_t en = __shfl_sync(0xffffffffu, (v << 16) | (r << 12) | ((off >> 1) + j), __ffs(m) - 1);
          m &= m - 1;
          if (lane == (int)c) exc = en;
          c++;
        }
      }
    }
  }
  if (ok) cnt = c;
  return ok;
}

__device__ __forceinline__ void pack4(uint32_t& p0, uint32_t& p1, uint32_t& p2, uint32_t w0, uint32_t w1, uint32_t w2,
                                      uint32_t w3, uint32_t nb) {
  const uint32_t x0 = __viaddmax_s16x2(w0 & ~PK_S, nb, 0u), x1 = __viaddmax_s16x2(w1 & ~PK_S, nb, 0u);
  const uint32_t x2 = __viaddmax_s16x2(w2 & ~PK_S, nb, 0u), x3 = __viaddmax_s16x2(w3 & ~PK_S, nb, 0u);
  p0 = x0 | (w0 & PK_S) | ((x3 << 11) & PK_M);
  p1 = x1 | (w1 & PK_S) | ((x3 << 7) & PK_M);
  p2 = x2 | (w2 & PK_S) | ((x3 << 3) & 0x38003800u) | ((w3 >> 1) & 0x40004000u);
}
__device__ __forceinline__ void unpack4_store(uint32_t addr, uint32_t p0, uint32_t p1, uint32_t p2, uint32_t thr) {
  const uint32_t x3 = ((p0 >> 11) & 0x000f000fu) | ((p1 >> 7) & 0x00f000f0u) | ((p2 >> 3) & 0x07000700u);
  sts128(addr, (p0 & ~PK_M) + __vminu2(p0 & 0x07ff07ffu, 0x00010001u) * thr,
         (p1 & ~PK_M) + __vminu2(p1 & 0x07ff07ffu, 0x00010001u) * thr,
         (p2 & ~PK_M) + __vminu2(p2 & 0x07ff07ffu, 0x00010001u) * thr,
         (x3 | ((p2 << 1) & PK_S)) + __vminu2(x3, 0x00010001u) * thr);
}
__device__ __forceinline__ uint32_t neg_base(uint32_t b) { return ((0u - (b << 7)) & 0xffffu) * 0x00010001u; }

__device__ __forceinline__ void grab_tile(uint32_t (&p)[48], uint32_t src) {
#pragma unroll
  for (int i = 0; i < 48; i++) p[i] = lds32(src + i * 128);
}
__device__ __forceinline__ void drop_tile(const uint32_t (&p)[48], uint32_t dst) {
#pragma unroll
  for (int i = 0; i < 48; i++) sts32(dst + i * 128, p[i]);
}
__device__ __forceinline__ void pack_tile_smem(uint32_t pk, uint32_t pv, uint32_t img, int lane, uint32_t bases) {
#pragma unroll 1
  for (int h = 0; h < 4; h++) {
    const uint32_t nb = neg_base((bases >> (8 * (h >> 1))) & 0xffu);
    const uint32_t src = img + h * 2048 + lane * 16, dst = ((h & 2) ? pv : pk) + (h & 1) * 1536 + lane * 4;
    uint32_t p[12];
#pragma unroll
    for (int i = 0; i < 4; i++) {
      uint32_t w0, w1, w2, w3;
      lds128(w0, w1, w2, w3, src + i * 512);
      pack4(p[3 * i], p[3 * i + 1], p[3 * i + 2], w0, w1, w2, w3, nb);
    }
    __syncwarp();
#pragma unroll
    for (int i = 0; i < 12; i++) sts32(dst + i * 128, p[i]);
  }
}
__device__ __forceinline__ void unpack_tile_smem(uint32_t pk, uint32_t pv, uint32_t img, int lane, uint32_t bases) {
#pragma unroll 1
  for (int h = 0; h < 4; h++) {
    const uint32_t thr = ((bases >> (8 * (h >> 1))) & 0xffu) << 7;
    const uint32_t dst = img + h * 2048 + lane * 16, src = ((h & 2) ? pv : pk) + (h & 1) * 1536 + lane * 4;
    uint32_t p[12];
#pragma unroll
    for (int i = 0; i < 12; i++) p[i] = lds32(src + i * 128);
    __syncwarp();
#pragma unroll
    for (int i = 0; i < 4; i++) unpack4_store(dst + i * 512, p[3 * i], p[3 * i + 1], p[3 * i + 2], thr);
  }
}

template <int H>
__device__ __forceinline__ void w_frags(uint32_t (&A)[32], uint32_t seg, int lane) {
  const int row = (lane & 7) + ((lane >> 4) << 3);
  const uint32_t base = seg + row * 64 + ((((lane >> 3) & 1) ^ ((row >> 1) & 3)) << 4);
#pragma unroll
  for (int i = 0; i < 4; i++)
    ldsm4t(A[16 * H + 4 * i], A[16 * H + 4 * i + 1], A[16 * H + 4 * i + 2], A[16 * H + 4 * i + 3],
           (base ^ ((i & 1) << 5)) + (i >> 1) * 1024);
}

template <int NKS, bool LN, int FMT>
__device__ __forceinline__ void gemv_regs(const uint32_t (&A)[32], uint32_t sb, int warp, int lane, uint32_t xw,
                                          uint32_t* dst, bool real) {
  float acc[2][4] = {{0.f, 0.f, 0.f, 0.f}, {0.f, 0.f, 0.f, 0.f}};
  const int t = lane & 3, g = lane >> 2;
  float s1 = lo16(xw) + hi16(xw), s2 = fmaf(lo16(xw), lo16(xw), hi16(xw) * hi16(xw));
#pragma unroll
  for (int ks = 0; ks < NKS; ks++) {
    const uint32_t x0 = __shfl_sync(0xffffffffu, xw, 8 * ks + t);
    const uint32_t x1 = __shfl_sync(0xffffffffu, xw, 8 * ks + 4 + t);
    const uint32_t b0 = (LN && (g & 1)) ? 0x3f803f80u : x0, b1 = (LN && (g & 1)) ? 0x3f803f80u : x1;
    mma(acc[0], A[8 * ks], A[8 * ks + 1], A[8 * ks + 2], A[8 * ks + 3], b0, b1);
    mma(acc[1], A[8 * ks + 4], A[8 * ks + 5], A[8 * ks + 6], A[8 * ks + 7], b0, b1);
    if (LN) {
      s1 += __shfl_xor_sync(0xffffffffu, s1, 16 >> ks);
      s2 += __shfl_xor_sync(0xffffffffu, s2, 16 >> ks);
    }
  }
  if (LN) {
    s1 += __shfl_xor_sync(0xffffffffu, s1, 1);
    s2 += __shfl_xor_sync(0xffffffffu, s2, 1);
  }
  const float v = (t & 2) ? ((t & 1) ? acc[1][2] : acc[1][0]) : ((t & 1) ? acc[0][2] : acc[0][0]);
  if (LN) {
    const float cs = (t & 2) ? ((t & 1) ? acc[1][3] : acc[1][1]) : ((t & 1) ? acc[0][3] : acc[0][1]);
    stsf2(sb + SM_Q + (warp * 32 + 8 * t + g) * 8, v, cs);
    if (lane == 0) stsf2(sb + SM_STAT + warp * 8, s2, s1);
  } else {
    stsf(sb + SM_Q + (warp * 32 + 8 * t + g) * 4, v);
  }
  dst = pin(dst);
  uint32_t ra = sb + SM_Q + lane * (LN ? 8 : 4);
  asm volatile("" : "+r"(ra));
  __syncthreads();
  if (warp == 0) {
    float y;
    if (LN) {
      float u[8], c[8], q[8], m[8];
#pragma unroll
      for (int w = 0; w < 8; w++) ldsf2(q[w], m[w], sb + SM_STAT + w * 8);
#pragma unroll
      for (int w = 0; w < 8; w++) ldsf2(u[w], c[w], ra + w * 256);
      const float mean = (((m[0] + m[1]) + (m[2] + m[3])) + ((m[4] + m[5]) + (m[6] + m[7]))) * (1.f / 512.f);
      const float msq = (((q[0] + q[1]) + (q[2] + q[3])) + ((q[4] + q[5]) + (q[6] + q[7]))) * (1.f / 512.f);
      const float vb = rbf(fmaxf(fmaf(-mean, mean, msq), 0.f));
      float sq, rs;
      asm("sqrt.approx.ftz.f32 %0, %1;" : "=f"(sq) : "f"(rbf(vb + 1e-5f)));
      asm("rcp.approx.ftz.f32 %0, %1;" : "=f"(rs) : "f"(rbf(sq)));
      y = ((u[0] + u[1]) + (u[2] + u[3])) + ((u[4] + u[5]) + (u[6] + u[7]));
      const float cs = ((c[0] + c[1]) + (c[2] + c[3])) + ((c[4] + c[5]) + (c[6] + c[7]));
      y = fmaf(-rbf(mean), cs, y) * rs;
    } else {
      float u[8];
#pragma unroll
      for (int w = 0; w < 8; w++) u[w] = ldsf(ra + w * 128);
      y = ((u[0] + u[1]) + (u[2] + u[3])) + ((u[4] + u[5]) + (u[6] + u[7]));
    }
    uint32_t o;
    if (FMT == 2) o = pack2(y, __shfl_down_sync(0xffffffffu, y, 1));
    else o = __float_as_uint(FMT == 1 ? rbf(y) : y);
    o = enc(o);
    asm volatile("{.reg .pred p; setp.ne.u32 p, %2, 0; @p st.relaxed.gpu.global.u32 [%0], %1;}"
                 ::"l"(dst), "r"(o), "r"((uint32_t)(real && (FMT != 2 || !(lane & 1)))) : "memory");
  }
}

template <int NP, class F, class G>
__device__ __forceinline__ uint32_t add_partials(const uint32_t* p, uint32_t xw, bool real, F side, G after) {
  uint32_t a[NP], b[NP];
#pragma unroll
  for (int k = 0; k < NP; k++) a[k] = b[k] = 0u;
  int it = 0;
  bool pend, done = false;
  if (real) do {
#pragma unroll
    for (int k = 0; k < NP; k++)
      if (a[k] == 0u || b[k] == 0u) ldr64(a[k], b[k], p + k * 512);
    if (!done) done = side();
    const uint32_t m0 = __vimin3_u32(__vimin3_u32(a[0], b[0], a[1]), __vimin3_u32(b[1], a[2], b[2]), __vimin3_u32(a[3], b[3], a[4]));
    const uint32_t m1 = __vimin3_u32(__vimin3_u32(b[4], a[5], b[5]), __vimin3_u32(a[6], b[6], a[NP - 1]), b[NP - 1]);
    pend = min(m0, m1) == 0u;
    if (!done) done = side();
    if (++it > SPIN_LIMIT) __trap();
  } while (__any_sync(0xffffffffu, pend) || !done);
  auto f = [](uint32_t u) { return __uint_as_float(u); };
  float y0 = ((f(a[0]) + f(a[1])) + (f(a[2]) + f(a[3]))) + ((f(a[4]) + f(a[5])) + (NP == 8 ? f(a[6]) + f(a[NP - 1]) : f(a[6])));
  float y1 = ((f(b[0]) + f(b[1])) + (f(b[2]) + f(b[3]))) + ((f(b[4]) + f(b[5])) + (NP == 8 ? f(b[6]) + f(b[NP - 1]) : f(b[6])));
  asm volatile("" : "+f"(y0), "+f"(y1));
  after();
  return pack2(lo16(xw) + rbf(y0), hi16(xw) + rbf(y1));
}

__global__ void __launch_bounds__(NTHR, 1)
decode_kernel(const __grid_constant__ Maps maps, const uint32_t* __restrict__ x_in,
              const char* __restrict__ Kp, const char* __restrict__ Vp, uint32_t* __restrict__ out) {
  extern __shared__ __align__(1024) unsigned char smem[];
  const uint32_t sb = (uint32_t)__cvta_generic_to_shared(smem);
  const int tid = threadIdx.x, lane = tid & 31;
  const int warp = __shfl_sync(0xffffffffu, tid >> 5, 0);
  const int cta = blockIdx.x;
  const int head_lo = cta < 128 ? ((cta + 3 * (cta >> 3)) & 7) : 2 * (cta - 128), head_hi = cta < 128 ? head_lo : head_lo + 1;
  const int head = warp < 4 ? head_lo : head_hi;
  const int jw = cta < 128 ? (cta >> 3) * 8 + warp : 128 + (warp & 3);
  const uint32_t ring = sb + warp * WARP_BYTES;
  const uint32_t rbar = sb + SM_BAR + warp * 40;
  const uint32_t wbar = rbar + 24;
  const uint32_t wseg = ring + O_W;

  auto w_issue = [&](int half, const CUtensorMap* m, int col, int row) {
    if (lane == 0) {
      mbar_expect(wbar + half * 8, 2048);
      tma2d(wseg + half * 2048, m, col, row, wbar + half * 8, pol_evict_first());
    }
    __syncwarp();
  };
  auto issue_demote = [&](int sl, int t) {
    if (lane == 0) {
      uint64_t pn;
      asm volatile("createpolicy.fractional.L2::evict_normal.b64 %0, 1.0;" : "=l"(pn));
      const uint64_t pf = pol_evict_first();
      const int row = head * SK + t * 16;
      const uint32_t dst = ring + sl * SLOT_BYTES, b = rbar + sl * 8;
      mbar_expect(b, SLOT_BYTES);
      tma3d(dst, &maps.k, row, b, pn);
      asm volatile("cp.async.bulk.prefetch.L2.global.L2::cache_hint [%0], %1, %2;" ::"l"(Kp + (size_t)row * 256), "r"(4096), "l"(pf) : "memory");
      tma3d(dst + 4096, &maps.v, row, b, pn);
      asm volatile("cp.async.bulk.prefetch.L2.global.L2::cache_hint [%0], %1, %2;" ::"l"(Vp + (size_t)row * 256), "r"(4096), "l"(pf) : "memory");
    }
    __syncwarp();
  };
  auto issue = [&](int sl, int t, bool kp) {
    if (lane == 0) {
      const uint64_t pf = pol_evict_first();
      const int row = head * SK + t * 16;
      const uint32_t dst = ring + sl * SLOT_BYTES, b = rbar + sl * 8;
      mbar_expect(b, SLOT_BYTES);
      tma3d(dst, &maps.k, row, b, pf);
      if (kp) l2_prefetch(Kp + (size_t)row * 256, 4096);
      tma3d(dst + 4096, &maps.v, row, b, pf);
      if (kp) l2_prefetch(Vp + (size_t)row * 256, 4096);
    }
    __syncwarp();
  };
  auto stack_tile = [&](uint32_t r) -> int { return r == 5 ? 6 * WPH + (jw >> 1) : jw + (r == 6 ? 5 : (int)r) * WPH; };

  uint32_t xw = __ldg(x_in + tid);
  if (lane == 0) {
    if (sb & 1023) __trap();
#pragma unroll
    for (int i = 0; i < 5; i++) mbar_init(rbar + i * 8, 1);
    asm volatile("fence.mbarrier_init.release.cluster;" ::: "memory");
    fence_async();
  }
  if (cta < 128) { w_issue(0, &maps.wq, cta * 32, warp * 64); w_issue(1, &maps.wq, cta * 32, warp * 64 + 32); }
  if (tid == 0 && cta < 128 && (cta & 15) == 0) {
    g_s.ctr[0][cta >> 4][0] = 0;
    asm volatile("fence.acq_rel.gpu;" ::: "memory");
  }
  __syncwarp();
  issue_demote(2, jw);
  if (tid == 32) {
    asm volatile("prefetch.tensormap [%0];" ::"l"(&maps.wo) : "memory");
    asm volatile("prefetch.tensormap [%0];" ::"l"(&maps.wg) : "memory");
    asm volatile("prefetch.tensormap [%0];" ::"l"(&maps.wu) : "memory");
    asm volatile("prefetch.tensormap [%0];" ::"l"(&maps.wd) : "memory");
  }
  __syncwarp();

  uint32_t c0[48], c1[48], c2[48], c3[48];
#pragma unroll
  for (int i = 0; i < 48; i++) { c0[i] = 0; c1[i] = 0; c2[i] = 0; c3[i] = 0; }
  uint32_t exc = 0;

  uint32_t sst = 0;

  for (int layer = -1; layer < 2; layer++) {
    const bool live = layer >= 0;
    const int ly = live ? layer : 0;

    if (live) {
      Attn st;
#pragma unroll
      for (int i = 0; i < 4; i++) { st.o[i][0] = st.o[i][1] = st.o[i][2] = st.o[i][3] = 0.f; }
      st.m0 = st.m1 = -INFINITY; st.l0 = st.l1 = 0.f;
      const int ln = fresh_lane();
      const uint32_t koff = ((ln & 7) + ((ln >> 3) & 1) * 8) * 128 + (((ln >> 4) ^ (ln & 7)) << 4);
      const uint32_t voff = 4096 + (ln >> 4) * 2048 + (ln & 7) * 128 + ((((ln >> 3) & 1) ^ (ln & 7)) << 4);
      const uint32_t qaddr = sb + SM_Q + ((head - head_lo) * 4 + (ln & 3)) * Q_PITCH + (ln >> 3) * 16;
      const bool lowg = ln < 16;
      int nxt = jw - NSTAT * WPH;
      if (layer == 0) { sst = 7; nxt += WPH; }
      else sst = ((sst ^ 0x10) & 0x3ff0770) | 1;
      while (true) {
        int sl = -1;
        if ((sst & 2) && mbar_test(rbar + 8, (sst >> 5) & 1)) sl = 1;
        if (sst & 4) sl = 2;
        if ((sst & 1) && mbar_test(rbar, (sst >> 4) & 1)) sl = 0;
        sl = __shfl_sync(0xffffffffu, sl, 0);
        if (sl >= 0) {
          tile_smem(st, ring + sl * SLOT_BYTES + koff, ring + sl * SLOT_BYTES + voff, qaddr, lowg);
          __syncwarp();
          sst ^= 0x11u << sl;
          if (sl == 0) sst |= 0x2000;
          if (layer == 0) {
            if (sl != 0 || (sst & 0x8000)) {
              const int l_ = fresh_lane();
              const uint32_t r = (sst >> 8) & 7, img = ring + sl * SLOT_BYTES;
              uint32_t bases, cnt = (sst >> 21) & 31;
              if (!pack_prepare(img, l_, r, bases, exc, cnt)) bases |= 0x10000;
              sst = ((sst & ~(31u << 21) & ~0x8000u) | (cnt << 21)) + ((r == 4 && (warp & 1)) ? 0x200 : 0x100);
              if (l_ == EXC_CAP + (int)r) exc = bases;
              const uint32_t pk = r < 4 ? img : ring + (r == 4 ? O_C1 : r == 5 ? O_E : O_C0);
              pack_tile_smem(pk, pk + (r == 5 ? WARP_BYTES : 3072), img, l_, bases);
              if (r == 0) grab_tile(c0, img + l_ * 4);
              else if (r == 1) grab_tile(c1, img + l_ * 4);
              else if (r == 2) grab_tile(c2, img + l_ * 4);
              else if (r == 3) grab_tile(c3, img + l_ * 4);
              fence_async();
              __syncwarp();
              if (sl == 1 && (sst & 0x700) < 0x600) { issue(1, stack_tile((sst >> 8) & 7), false); sst |= 2; }
            }
          } else if (sl == 1 && ((sst >> 16) & 31)) {
            sst -= 1u << 16;
            uint32_t t;
            asm volatile("ld.shared.u16 %0, [%1];" : "=r"(t) : "r"(sb + SM_LIST + warp * (KCAP * 2) + ((sst >> 16) & 31) * 2) : "memory");
            issue(1, t, false); sst |= 2;
          }
        } else if (layer == 1 && (sst & 0x700) && !(sst & 2) && ((sst & 0x2000) || !(sst & 1))) {
          const int l_ = fresh_lane();
          const uint32_t r = ((sst >> 8) & 7) - 1, img = ring + SLOT_BYTES;
          sst = ((sst - ((r == 6 && (warp & 1)) ? 0x200 : 0x100)) | 2) & ~0x2000u;
          const uint32_t hdr = __shfl_sync(0xffffffffu, exc, EXC_CAP + r);
          if (hdr & 0x10000) {
            issue(1, stack_tile(r), false);
          } else {
            const uint32_t pk = ring + (r <= 4 ? O_C1 : r == 5 ? O_E : O_C0);
            if (r == 0) drop_tile(c0, pk + l_ * 4);
            else if (r == 1) drop_tile(c1, pk + l_ * 4);
            else if (r == 2) drop_tile(c2, pk + l_ * 4);
            else if (r == 3) drop_tile(c3, pk + l_ * 4);
            unpack_tile_smem(pk, pk + (r == 5 ? WARP_BYTES : 3072), img, l_, hdr);
            __syncwarp();
            if (l_ < (int)((sst >> 21) & 31) && ((exc >> 12) & 7) == r)
              asm volatile("st.shared.u16 [%0], %1;" ::"r"(img + (exc & 0xfffu) * 2), "r"(exc >> 16) : "memory");
            fence_async();
            __syncwarp();
            if (l_ == 0) mbar_expect(rbar + 8, 0);
          }
          __syncwarp();
        } else if (warp == 7 && (sst & 0x88) == 8) {
          sst = (sst | 0x80) & ~0x2000u;
          const int l_ = fresh_lane(), c_ = opaque(cta), y_ = opaque(ly);
          const uint4 z = make_uint4(0, 0, 0, 0);
          const int s_lo = c_ >> 3;
          uint4* po = reinterpret_cast<uint4*>(&g_s.PO[y_][head_lo][s_lo][0]);
          po[l_] = z; po[l_ + 32] = z;
          if (l_ < 2) reinterpret_cast<uint4*>(&g_s.ML[y_][head_lo][s_lo][0])[l_] = z;
          if (head_hi != head_lo) {
            po = reinterpret_cast<uint4*>(&g_s.PO[y_][head_hi][16][0]);
            po[l_] = z; po[l_ + 32] = z;
            if (l_ < 2) reinterpret_cast<uint4*>(&g_s.ML[y_][head_hi][16][0])[l_] = z;
          }
          if (c_ < 128) {
            (&g_s.Y1[y_][0][0])[c_ * 32 + l_] = 0;
            if (y_ == 0 && l_ < 16) g_s.QX[1][c_ * 16 + l_] = 0;
          }
          if (c_ < 112) { g_s.GU[y_][c_ * 32 + l_] = 0; (&g_s.Y2[y_][0][0])[c_ * 32 + l_] = 0; }
          if (c_ < 8 && y_ == 0 && l_ == 0) g_s.ctr[1][c_][0] = 0;
          __syncwarp();
          if (l_ == 0) {
            asm volatile("fence.acq_rel.gpu;" ::: "memory");
            const uint32_t old = atomicAdd(&g_s.cnt[y_][0], 1u);
            sts32(sb + SM_STAT + 64, (old / NCTA + 1) * NCTA);
          }
          __syncwarp();
        } else if ((sst & 7) == 0) {
          break;
        } else if ((sst & 0x3080) == 0x2080) {
          uint32_t target, c;
          asm volatile("ld.shared.u32 %0, [%1];" : "=r"(target) : "r"(sb + SM_STAT + 64) : "memory");
          asm volatile("ld.acquire.gpu.global.u32 %0, [%1];" : "=r"(c) : "l"(&g_s.cnt[opaque(ly)][0]) : "memory");
          sst &= ~0x2000u;
          if (__all_sync(0xffffffffu, (int)(c - target) >= 0)) sst |= 0x1000;
        } else {
          int it = 0;
          while (!__any_sync(0xffffffffu, ((sst & 1) && mbar_test(rbar, (sst >> 4) & 1)) || ((sst & 2) && mbar_test(rbar + 8, (sst >> 5) & 1))))
            if (++it > (SPIN_LIMIT << 3)) __trap();
        }
        if (!(sst & 0x801)) {
          if (layer == 0 && (sst & 0x700) == 0x600) {
            issue(0, stack_tile(6), false); sst |= 0x8001;
          } else {
            const int d = __shfl_sync(0xffffffffu, nxt, 8) + NSTAT * WPH;
            const int nd = layer == 0 ? N_ALL : N_DYN;
            if (d >= nd - RESET_X) sst |= 8;
            if (d < nd) {
              const bool kp = d >= N_DYN;
              issue(0, T_DYN + d, kp); sst |= 1;
              if (kp) {
                if (lane == 0)
                  asm volatile("st.shared.u16 [%0], %1;" ::"r"(sb + SM_LIST + warp * (KCAP * 2) + ((sst >> 16) & 31) * 2), "r"(T_DYN + d) : "memory");
                sst += 1u << 16;
              }
              const bool full = (layer == 0 && ((sst >> 16) & 31) == KCAP) || ((warp & 3) == 0 && d >= nd - STOP_X), stat = d < (NSTAT - 1) * WPH;
              nxt = full ? 1 << 20 : d - (NSTAT - 1) * WPH;
              if (layer == 0 && !stat && d < NSTAT * WPH) {
                uint32_t qw;
                asm volatile("ld.acquire.gpu.global.u32 %0, [%1];" : "=r"(qw) : "l"(&g_s.QX[0][head * 256]) : "memory");
              }
              asm volatile("{.reg .pred p; setp.ne.u32 p, %2, 0; @p atom.global.relaxed.gpu.inc.u32 %0, [%1], 0x7fffffff;}"
                           : "+r"(nxt) : "l"(&g_s.ctr[layer][head][0]), "r"((uint32_t)(lane == 8 && !full && !stat)) : "memory");
              __syncwarp();
            } else if (layer == 1) {
              sst |= 0x800;
            } else if ((sst & 0x700) == 0x700) {
              issue(0, T_LAST + jw, false); sst |= 0x801;
            }
          }
        }
      }
      int rank = __shfl_sync(0xffffffffu, nxt, 8) + NSTAT * WPH - (layer == 0 ? N_ALL : N_DYN);

      {
#pragma unroll
        for (int o = 4; o <= 16; o <<= 1) {
          st.l0 += __shfl_xor_sync(0xffffffffu, st.l0, o);
          st.l1 += __shfl_xor_sync(0xffffffffu, st.l1, o);
        }
        const int g = lane >> 2, t = lane & 3;
        const uint32_t a = ring + O_P + ((t & 1) * 128 + (t >> 1) * 64) * 4;
#pragma unroll
        for (int mt = 0; mt < 4; mt++) {
          sts32(a + ((16 * mt + g) ^ (8 * t)) * 4, pack2(st.o[mt][0], st.o[mt][1]));
          sts32(a + ((16 * mt + 8 + g) ^ (8 * t)) * 4, pack2(st.o[mt][2], st.o[mt][3]));
        }
        if (lane < 2)
          sts128(sb + SM_ML + warp * 32 + lane * 16, __float_as_uint(st.m0), __float_as_uint(st.l0),
                 __float_as_uint(st.m1), __float_as_uint(st.l1));
      }
      {
        const int hp = tid >> 7, d = tid & 127, odd = tid & 1, hq = 2 * hp + odd;
        uint32_t* ppo = pin(&g_s.PO[ly][head_lo][cta >> 3][hq * 64 + (d >> 1)]);
        uint32_t* pml = pin(&g_s.ML[ly][head_lo][cta >> 3][2 * hq]);
        uint32_t am = sb + SM_ML + hp * 16 + odd * 8;
        uint32_t ap = sb + O_P + (hp * 128 + ((d & ~1) ^ (8 * (hp + 2 * (d >> 6))))) * 4;
        uint32_t sel = odd ? 0x7632 : 0x5410;
        asm volatile("" : "+r"(am), "+r"(ap), "+r"(sel));
        if (cta < 128) {
          if (rank > 100000) rank = STOP_R;
          if (rank < WO_R0) {
            const uint32_t c0_ = clock();
            while (__any_sync(0xffffffffu, (uint32_t)clock() - c0_ < (uint32_t)((WO_R0 - rank) * WO_K))) {}
          }
          w_issue(0, &maps.wo, (cta & 15) * 32, (cta >> 4) * 512 + warp * 64);
        }
        __syncthreads();
        float mw[8], lw[8];
        uint32_t u[8];
#pragma unroll
        for (int w = 0; w < 8; w++) ldsf2(mw[w], lw[w], am + w * 32);
#pragma unroll
        for (int w = 0; w < 8; w++) {
          uint32_t x0, x1;
          asm volatile("ld.shared.v2.u32 {%0,%1}, [%2];" : "=r"(x0), "=r"(x1) : "r"(ap + w * WARP_BYTES) : "memory");
          u[w] = __byte_perm(x0, x1, sel);
        }
        const bool split = head_hi != head_lo;
        float Ma = fmaxf(fmaxf(mw[0], mw[1]), fmaxf(mw[2], mw[3]));
        float Mb = fmaxf(fmaxf(mw[4], mw[5]), fmaxf(mw[6], mw[7]));
        if (!split) Ma = Mb = fmaxf(Ma, Mb);
        float La = 0.f, a0 = 0.f, a1 = 0.f, Lb = 0.f, b0 = 0.f, b1 = 0.f;
#pragma unroll
        for (int w = 0; w < 4; w++) {
          const float ea = ex2(mw[w] - Ma), eb = ex2(mw[w + 4] - Mb);
          La = fmaf(lw[w], ea, La); a0 = fmaf(lo16(u[w]), ea, a0); a1 = fmaf(hi16(u[w]), ea, a1);
          Lb = fmaf(lw[w + 4], eb, Lb); b0 = fmaf(lo16(u[w + 4]), eb, b0); b1 = fmaf(hi16(u[w + 4]), eb, b1);
        }
        if (!split) { La += Lb; a0 += b0; a1 += b1; }
        if (d < 2) str64(pml, enc(__float_as_uint(Ma)), enc(__float_as_uint(La)));
        const float ia = rcp(La);
        str32(ppo, enc(pack2(a0 * ia, a1 * ia)));
        if (split) {
          if (d < 2) str64(pml + 17 * 8, enc(__float_as_uint(Mb)), enc(__float_as_uint(Lb)));
          const float ib = rcp(Lb);
          str32(ppo + 17 * 256, enc(pack2(b0 * ib, b1 * ib)));
        }
      }
      if (cta < 128) w_issue(1, &maps.wo, (cta & 15) * 32, (cta >> 4) * 512 + warp * 64 + 32);
      if (tid == 255 && !(sst & 0x1000)) {
        uint32_t target, c;
        asm volatile("ld.shared.u32 %0, [%1];" : "=r"(target) : "r"(sb + SM_STAT + 64) : "memory");
        int it = 0;
        do {
          asm volatile("ld.acquire.gpu.global.u32 %0, [%1];" : "=r"(c) : "l"(&g_s.cnt[ly][0]) : "memory");
          if (++it > SPIN_LIMIT) __trap();
        } while ((int)(c - target) < 0);
      }
      __syncwarp();
      __syncthreads();
    }

    if (cta < 128) {
      uint32_t A[32];
      if (live) {
#pragma unroll 1
        for (int real = 0; real < 2; real++) {
#pragma unroll
          for (int i = 0; i < 16; i++) A[i] = 0u;
          const int rb = cta >> 4;
          const uint32_t* pp = pin(&g_s.PO[ly][rb][0][tid]);
          const uint32_t* pm = pin(&g_s.ML[ly][rb][lane < 17 ? lane : 0][2 * (warp >> 1)]);
          uint32_t v[17], um = 0u, ul = 0u;
#pragma unroll
          for (int s = 0; s < 17; s++) v[s] = 0u;
          int it = 0;
          bool pend, done = false;
          if (real) {
            do {
              if (um == 0u || ul == 0u) ldr64(um, ul, pm);
#pragma unroll
              for (int s = 0; s < 17; s++)
                if (v[s] == 0u) v[s] = ldr32(pp + s * 256);
              if (!done && __all_sync(0xffffffffu, mbar_test(wbar, 1))) {
                w_frags<0>(A, wseg, lane);
                __syncwarp();
                if (cta < 112) w_issue(0, cta < 56 ? &maps.wg : &maps.wu, (cta < 56 ? cta : cta - 56) * 32, warp * 64);
                else if (layer == 0) w_issue(0, &maps.wq, cta * 32, warp * 64);
                done = true;
              }
              pend = __vimin3_u32(__vimin3_u32(__vimin3_u32(um, ul, v[0]), __vimin3_u32(v[1], v[2], v[3]), __vimin3_u32(v[4], v[5], v[6])),
                                  __vimin3_u32(__vimin3_u32(v[7], v[8], v[9]), __vimin3_u32(v[10], v[11], v[12]), __vimin3_u32(v[13], v[14], v[15])), v[16]) == 0u;
              if (++it > SPIN_LIMIT) __trap();
            } while (__any_sync(0xffffffffu, pend) || !done);
          }
          const float ms = __uint_as_float(um);
          int mi = __float_as_int(ms);
          mi = __reduce_max_sync(0xffffffffu, mi ^ ((mi >> 31) & 0x7fffffff));
          const float M = __int_as_float(mi ^ ((mi >> 31) & 0x7fffffff));
          const float e = lane < 17 ? __uint_as_float(ul) * ex2(ms - M) : 0.f;
          float L = 0.f, o0 = 0.f, o1 = 0.f, Lb = 0.f, p0 = 0.f, p1 = 0.f;
#pragma unroll
          for (int s = 0; s < 17; s++) {
            const float es = __shfl_sync(0xffffffffu, e, s);
            if (s & 1) { Lb += es; p0 = fmaf(es, lo16(v[s]), p0); p1 = fmaf(es, hi16(v[s]), p1); }
            else { L += es; o0 = fmaf(es, lo16(v[s]), o0); o1 = fmaf(es, hi16(v[s]), o1); }
          }
          o0 += p0; o1 += p1;
          asm volatile("" : "+f"(o0), "+f"(o1));
          if (real) mbar_wait(wbar + 8, cta < 112 ? layer ^ 1 : 1);
          w_frags<1>(A, wseg + 2048, lane);
          const float inv = rcp(L + Lb);
          gemv_regs<4, false, 0>(A, sb, warp, lane, pack2(o0 * inv, o1 * inv), &g_s.Y1[ly][0][0] + cta * 32 + lane, real);
          if (real) {
            if (cta < 112) w_issue(1, cta < 56 ? &maps.wg : &maps.wu, (cta < 56 ? cta : cta - 56) * 32, warp * 64 + 32);
            else if (layer == 0) w_issue(1, &maps.wq, cta * 32, warp * 64 + 32);
          }
          __syncthreads();
        }
#pragma unroll 1
        for (int real = 0; real < 2; real++) {
#pragma unroll
          for (int i = 0; i < 16; i++) A[i] = 0u;
          const uint32_t xn = add_partials<8>(pin(&g_s.Y1[ly][0][2 * tid]), xw, real, [&]() {
            if (cta >= 112) return true;
            if (!__all_sync(0xffffffffu, mbar_test(wbar, 0))) return false;
            w_frags<0>(A, wseg, lane);
            __syncwarp();
            w_issue(0, &maps.wd, (cta & 15) * 32, (cta >> 4) * 256 + warp * 32);
            return true;
          }, [&]() { if (real && cta < 112) mbar_wait(wbar + 8, layer); w_frags<1>(A, wseg + 2048, lane); });
          if (real) { xw = xn; }
          if (cta < 112) {
            gemv_regs<4, true, 1>(A, sb, warp, lane, xn, &g_s.GU[ly][cta * 32 + lane], real);
            if (real) {
              if (layer == 0) {
                w_issue(1, &maps.wq, cta * 32, warp * 64 + 32);
              }
            }
            __syncthreads();
          }
        }
        if (cta < 112) {
#pragma unroll 1
          for (int real = 0; real < 2; real++) {
#pragma unroll
            for (int i = 0; i < 16; i++) A[i] = 0u;
            const uint32_t* pg = pin(&g_s.GU[ly][(lane >> 4) * FF + (cta >> 4) * 256 + warp * 32 + (lane & 15) * 2]);
            uint32_t a = 0u, b = 0u;
            int it = 0;
            bool done = false;
            if (real) {
              do {
                if (a == 0u || b == 0u) ldr64(a, b, pg);
                if (!done && __all_sync(0xffffffffu, mbar_test(wbar, 1))) {
                  w_frags<0>(A, wseg, lane);
                  __syncwarp();
                  if (layer == 0) { w_issue(0, &maps.wq, cta * 32, warp * 64); }
                  done = true;
                }
                if (++it > SPIN_LIMIT) __trap();
              } while (__any_sync(0xffffffffu, a == 0u || b == 0u) || !done);
            }
            const float a0 = __uint_as_float(a), a1 = __uint_as_float(b);
            const float c0_ = __shfl_xor_sync(0xffffffffu, a0, 16), c1_ = __shfl_xor_sync(0xffffffffu, a1, 16);
            const float g0 = lane < 16 ? a0 : c0_, g1 = lane < 16 ? a1 : c1_;
            const float u0 = lane < 16 ? c0_ : a0, u1 = lane < 16 ? c1_ : a1;
            const uint32_t hw = pack2((g0 > 0.f ? g0 : g0 * 0.f) * u0, (g1 > 0.f ? g1 : g1 * 0.f) * u1);
            gemv_regs<2, false, 0>(A, sb, warp, lane, hw, &g_s.Y2[ly][0][0] + cta * 32 + lane, real);
            __syncthreads();
          }
        }
        if (layer == 1 && cta != 127) break;
        if (layer == 0 && warp == 4) {
          if (lane < 16) g_s.QX[0][cta * 16 + lane] = 0;
          __syncwarp();
        }
      }
#pragma unroll 1
      for (int real = live ? 0 : 1; real < 2; real++) {
#pragma unroll
        for (int i = 0; i < 16; i++) A[i] = 0u;
        if (!live) {
          mbar_wait(wbar, 0); mbar_wait(wbar + 8, 0);
          w_frags<0>(A, wseg, lane);
        }
        const uint32_t xn = add_partials<7>(pin(&g_s.Y2[ly][0][2 * tid]), xw, real && live, [&]() {
          if (layer == 1) return true;
          if (!__all_sync(0xffffffffu, mbar_test(wbar, 0) && mbar_test(wbar + 8, cta < 112 ? 1 : 0))) return false;
          w_frags<0>(A, wseg, lane);
          return true;
        }, [&]() { w_frags<1>(A, wseg + 2048, lane); });
        if (real && live) {
          xw = xn;
          if (layer == 1) { out[tid] = xn; return; }
        }
        gemv_regs<4, true, 2>(A, sb, warp, lane, xw, &g_s.QX[(layer + 1) & 1][cta * 16 + (lane >> 1)], real);
        if (!real) __syncthreads();
      }
    } else if (layer == 1) {
      break;
    }
    if (!live) {
      mbar_wait(rbar + 16, 0);
      issue_demote(1, jw + WPH);
    }
    __syncthreads();
    {
      const uint32_t* pq = &g_s.QX[layer + 1][head_lo * 256 + tid];
      uint32_t qv0 = 0u, qv1 = head_hi != head_lo ? 0u : 1u;
      int it = 0;
      do {
        if (qv0 == 0u) qv0 = ldr32(pq);
        if (qv1 == 0u) qv1 = ldr32(pq + 256);
        if (++it > SPIN_LIMIT) __trap();
      } while (__any_sync(0xffffffffu, qv0 == 0u || qv1 == 0u));
      if (!live) issue_demote(0, T_DYN + jw);
      sts32(sb + SM_Q + (tid >> 6) * Q_PITCH + (tid & 63) * 4, qv0);
      sts32(sb + SM_Q + (4 + (tid >> 6)) * Q_PITCH + (tid & 63) * 4, qv1);
    }
    __syncthreads();
  }
}

typedef CUresult (*EncodeFn)(CUtensorMap*, CUtensorMapDataType, cuuint32_t, void*, const cuuint64_t*,
                             const cuuint64_t*, const cuuint32_t*, const cuuint32_t*, CUtensorMapInterleave,
                             CUtensorMapSwizzle, CUtensorMapL2promotion, CUtensorMapFloatOOBfill);

void make_kv_map(EncodeFn enc, CUtensorMap* m, void* p) {
  cuuint64_t dims[3] = {64, (cuuint64_t)8 * SK, 2};
  cuuint64_t strides[2] = {256, 128};
  cuuint32_t box[3] = {64, 16, 2}, es[3] = {1, 1, 1};
  enc(m, CU_TENSOR_MAP_DATA_TYPE_BFLOAT16, 3, p, dims, strides, box, es, CU_TENSOR_MAP_INTERLEAVE_NONE,
      CU_TENSOR_MAP_SWIZZLE_128B, CU_TENSOR_MAP_L2_PROMOTION_NONE, CU_TENSOR_MAP_FLOAT_OOB_FILL_NONE);
}
void make_w_map(EncodeFn enc, CUtensorMap* m, void* p, int rows, int cols) {
  cuuint64_t dims[2] = {(cuuint64_t)cols, (cuuint64_t)rows};
  cuuint64_t strides[1] = {(cuuint64_t)cols * 2};
  cuuint32_t box[2] = {32, 32}, es[2] = {1, 1};
  enc(m, CU_TENSOR_MAP_DATA_TYPE_BFLOAT16, 2, p, dims, strides, box, es, CU_TENSOR_MAP_INTERLEAVE_NONE,
      CU_TENSOR_MAP_SWIZZLE_64B, CU_TENSOR_MAP_L2_PROMOTION_NONE, CU_TENSOR_MAP_FLOAT_OOB_FILL_NONE);
}

}

extern "C" void kernel_launch(void* const* d_in, const int* in_sizes, int n_in, void* d_out, int out_size) {
  (void)in_sizes; (void)n_in; (void)out_size;
  void* fn = nullptr;
  cudaDriverEntryPointQueryResult qr;
  cudaGetDriverEntryPoint("cuTensorMapEncodeTiled", &fn, cudaEnableDefault, &qr);
  EncodeFn enc = (EncodeFn)fn;
  Maps maps;
  make_kv_map(enc, &maps.k, d_in[1]);
  make_kv_map(enc, &maps.v, d_in[2]);
  make_w_map(enc, &maps.wq, d_in[3], DM, 4096);
  make_w_map(enc, &maps.wo, d_in[4], 4096, DM);
  make_w_map(enc, &maps.wg, d_in[6], DM, FF);
  make_w_map(enc, &maps.wu, d_in[7], DM, FF);
  make_w_map(enc, &maps.wd, d_in[8], FF, DM);
  cudaFuncSetAttribute(decode_kernel, cudaFuncAttributeMaxDynamicSharedMemorySize, SM_TOTAL);
  decode_kernel<<<NCTA, NTHR, SM_TOTAL, cudaStreamPerThread>>>(
      maps, (const uint32_t*)d_in[0], (const char*)d_in[1], (const char*)d_in[2], (uint32_t*)d_out);
}
```

```cpp
#include <cuda_runtime.h>
#include <cuda_bf16.h>
#include <cuda.h>
#include <stdint.h>
#include <stdlib.h>

namespace {

constexpr int NCTA = 132, NWARP = 8, NTHR = 256;
constexpr int DM = 512, SK = 65536, FF = 1792;
constexpr int WPH = NCTA;
constexpr int SLOT_BYTES = 8192;
constexpr int KEEP_H = 760;
constexpr int RESET_X = 400;
constexpr int STOP_X = 700;
constexpr int WO_K = 25;
constexpr int WO_R0 = 60;
constexpr int STOP_R = -80;
constexpr int NSTAT = 2;
constexpr int T_DYN = 6 * 132 + 66;
constexpr int T_LAST = 4096 - 132;
constexpr int N_ALL = T_LAST - T_DYN;
constexpr int N_DYN = N_ALL - KEEP_H;
constexpr int KCAP = 12;
static_assert(KCAP * 99 > KEEP_H, "the warps that stream to the end must be able to take all kept tiles");
static_assert(N_DYN - STOP_X >= NSTAT * 132, "");

constexpr int WARP_BYTES = 28672;
constexpr int O_W = 8192, O_C0 = 12288, O_C1 = 18432, O_E = 24576, O_P = 27648;
constexpr int SM_BAR = NWARP * WARP_BYTES;
constexpr int SM_STAT = SM_BAR + 320;
constexpr int SM_Q = SM_STAT + 128;
constexpr int Q_PITCH = 272;
constexpr int SM_LIST = SM_Q + 2 * 4 * Q_PITCH;
constexpr int SM_ML = SM_LIST + NWARP * KCAP * 2;
constexpr int SM_TOTAL = SM_ML + NWARP * 32;
static_assert(SM_TOTAL <= 232448, "");

struct Scratch {
  uint32_t QX[2][2048];
  uint32_t PO[2][8][17][256];
  uint32_t ML[2][8][17][8];
  uint32_t Y1[2][8][512];
  uint32_t GU[2][2 * FF];
  uint32_t Y2[2][7][512];
  uint32_t cnt[2][32];
  uint32_t ctr[2][8][32];
};
__device__ __align__(1024) Scratch g_s;

struct Maps { CUtensorMap k, v, wq, wo, wg, wu, wd; };

constexpr int SPIN_LIMIT = 1 << 22;

__device__ __forceinline__ void mbar_init(uint32_t bar, int cnt) {
  asm volatile("mbarrier.init.shared::cta.b64 [%0], %1;" ::"r"(bar), "r"(cnt) : "memory");
}
__device__ __forceinline__ void mbar_expect(uint32_t bar, uint32_t bytes) {
  asm volatile("mbarrier.arrive.expect_tx.shared::cta.b64 _, [%0], %1;" ::"r"(bar), "r"(bytes) : "memory");
}
__device__ __forceinline__ void mbar_wait(uint32_t bar, uint32_t parity) {
  uint32_t ok;
  int it = 0;
  do {
    asm volatile("{.reg .pred p; mbarrier.try_wait.parity.shared::cta.b64 p, [%1], %2; selp.u32 %0,1,0,p;}"
                 : "=r"(ok) : "r"(bar), "r"(parity) : "memory");
    if (++it > SPIN_LIMIT) __trap();
  } while (!__all_sync(0xffffffffu, ok));
}
__device__ __forceinline__ bool mbar_test(uint32_t bar, uint32_t parity) {
  uint32_t ok;
  asm volatile("{.reg .pred p; mbarrier.test_wait.parity.shared::cta.b64 p, [%1], %2; selp.u32 %0,1,0,p;}"
               : "=r"(ok) : "r"(bar), "r"(parity) : "memory");
  return ok != 0;
}
__device__ __forceinline__ int fresh_lane() { int l; asm volatile("mov.u32 %0, %laneid;" : "=r"(l)); return l; }
template <class T> __device__ __forceinline__ T* pin(T* p) { asm volatile("" : "+l"(p)); return p; }
__device__ __forceinline__ int opaque(int x) { asm volatile("" : "+r"(x)); return x; }
__device__ __forceinline__ void tma3d(uint32_t dst, const CUtensorMap* m, int row, uint32_t bar, uint64_t pol) {
  asm volatile("cp.async.bulk.tensor.3d.shared::cluster.global.mbarrier::complete_tx::bytes.L2::cache_hint"
               " [%0], [%1, {%3, %4, %3}], [%2], %5;"
               ::"r"(dst), "l"(m), "r"(bar), "r"(0), "r"(row), "l"(pol) : "memory");
}
__device__ __forceinline__ void tma2d(uint32_t dst, const CUtensorMap* m, int col, int row, uint32_t bar, uint64_t pol) {
  asm volatile("cp.async.bulk.tensor.2d.shared::cluster.global.mbarrier::complete_tx::bytes.L2::cache_hint"
               " [%0], [%1, {%3, %4}], [%2], %5;"
               ::"r"(dst), "l"(m), "r"(bar), "r"(col), "r"(row), "l"(pol) : "memory");
}
__device__ __forceinline__ void l2_prefetch(const void* p, uint32_t bytes) {
  asm volatile("cp.async.bulk.prefetch.L2.global [%0], %1;" ::"l"(p), "r"(bytes) : "memory");
}
__device__ __forceinline__ uint64_t pol_evict_first() {
  uint64_t p;
  asm volatile("createpolicy.fractional.L2::evict_first.b64 %0, 1.0;" : "=l"(p));
  return p;
}
__device__ __forceinline__ void ldsm4(uint32_t& a, uint32_t& b, uint32_t& c, uint32_t& d, uint32_t addr) {
  asm volatile("ldmatrix.sync.aligned.m8n8.x4.shared.b16 {%0,%1,%2,%3}, [%4];"
               : "=r"(a), "=r"(b), "=r"(c), "=r"(d) : "r"(addr) : "memory");
}
__device__ __forceinline__ void ldsm4t(uint32_t& a, uint32_t& b, uint32_t& c, uint32_t& d, uint32_t addr) {
  asm volatile("ldmatrix.sync.aligned.m8n8.x4.trans.shared.b16 {%0,%1,%2,%3}, [%4];"
               : "=r"(a), "=r"(b), "=r"(c), "=r"(d) : "r"(addr) : "memory");
}
__device__ __forceinline__ void mma(float (&c)[4], uint32_t a0, uint32_t a1, uint32_t a2, uint32_t a3,
                                    uint32_t b0, uint32_t b1) {
  asm volatile("mma.sync.aligned.m16n8k16.row.col.f32.bf16.bf16.f32 {%0,%1,%2,%3}, {%4,%5,%6,%7}, {%8,%9}, {%0,%1,%2,%3};"
               : "+f"(c[0]), "+f"(c[1]), "+f"(c[2]), "+f"(c[3])
               : "r"(a0), "r"(a1), "r"(a2), "r"(a3), "r"(b0), "r"(b1));
}
__device__ __forceinline__ uint32_t movm(uint32_t a) {
  uint32_t d;
  asm volatile("movmatrix.sync.aligned.m8n8.trans.b16 %0, %1;" : "=r"(d) : "r"(a));
  return d;
}
__device__ __forceinline__ uint32_t pack2(float lo, float hi) {
  uint32_t d;
  asm("cvt.rn.bf16x2.f32 %0, %1, %2;" : "=r"(d) : "f"(hi), "f"(lo));
  return d;
}
__device__ __forceinline__ float lo16(uint32_t w) { return __uint_as_float(w << 16); }
__device__ __forceinline__ float hi16(uint32_t w) { return __uint_as_float(w & 0xffff0000u); }
__device__ __forceinline__ float rbf(float x) { return lo16(pack2(x, 0.f)); }
__device__ __forceinline__ float ex2(float x) {
  float y;
  asm("ex2.approx.ftz.f32 %0, %1;" : "=f"(y) : "f"(x));
  return y;
}
__device__ __forceinline__ float rcp(float x) {
  float y;
  asm("rcp.approx.ftz.f32 %0, %1;" : "=f"(y) : "f"(x));
  return y;
}
__device__ __forceinline__ uint32_t enc(uint32_t w) { return w ? w : 0x80000000u; }
__device__ __forceinline__ uint32_t ldr32(const uint32_t* p) {
  uint32_t v;
  asm volatile("ld.relaxed.gpu.global.u32 %0, [%1];" : "=r"(v) : "l"(p) : "memory");
  return v;
}
__device__ __forceinline__ void ldr64(uint32_t& a, uint32_t& b, const uint32_t* p) {
  asm volatile("ld.relaxed.gpu.global.v2.u32 {%0,%1}, [%2];" : "=r"(a), "=r"(b) : "l"(p) : "memory");
}
__device__ __forceinline__ void str32(uint32_t* p, uint32_t v) {
  asm volatile("st.relaxed.gpu.global.u32 [%0], %1;" ::"l"(p), "r"(v) : "memory");
}
__device__ __forceinline__ void str64(uint32_t* p, uint32_t a, uint32_t b) {
  asm volatile("st.relaxed.gpu.global.v2.u32 [%0], {%1,%2};" ::"l"(p), "r"(a), "r"(b) : "memory");
}
__device__ __forceinline__ void sts32(uint32_t addr, uint32_t v) {
  asm volatile("st.shared.u32 [%0], %1;" ::"r"(addr), "r"(v) : "memory");
}
__device__ __forceinline__ void stsf(uint32_t addr, float v) {
  asm volatile("st.shared.f32 [%0], %1;" ::"r"(addr), "f"(v) : "memory");
}
__device__ __forceinline__ void stsf2(uint32_t addr, float a, float b) {
  asm volatile("st.shared.v2.f32 [%0], {%1,%2};" ::"r"(addr), "f"(a), "f"(b) : "memory");
}
__device__ __forceinline__ float ldsf(uint32_t addr) {
  float v;
  asm volatile("ld.shared.f32 %0, [%1];" : "=f"(v) : "r"(addr) : "memory");
  return v;
}
__device__ __forceinline__ void ldsf2(float& a, float& b, uint32_t addr) {
  asm volatile("ld.shared.v2.f32 {%0,%1}, [%2];" : "=f"(a), "=f"(b) : "r"(addr) : "memory");
}
__device__ __forceinline__ void fence_async() { asm volatile("fence.proxy.async.shared::cta;" ::: "memory"); }

constexpr float SCALE_C = 0.08838834764831845f * 1.4426950408889634f;

struct Attn {
  float o[4][4];
  float m0, m1, l0, l1;
};

__device__ __forceinline__ void softmax_step(Attn& st, const float (&s)[4], uint32_t& r0, uint32_t& r1) {
  float t0 = fmaxf(s[0], s[2]), t1 = fmaxf(s[1], s[3]);
#pragma unroll
  for (int o = 4; o <= 16; o <<= 1) {
    t0 = fmaxf(t0, __shfl_xor_sync(0xffffffffu, t0, o));
    t1 = fmaxf(t1, __shfl_xor_sync(0xffffffffu, t1, o));
  }
  float n0 = fmaxf(st.m0, t0 * SCALE_C), n1 = fmaxf(st.m1, t1 * SCALE_C);
  float a0 = ex2(st.m0 - n0), a1 = ex2(st.m1 - n1);
  st.m0 = n0; st.m1 = n1;
  float p0 = ex2(fmaf(s[0], SCALE_C, -n0)), p1 = ex2(fmaf(s[1], SCALE_C, -n1));
  float p2 = ex2(fmaf(s[2], SCALE_C, -n0)), p3 = ex2(fmaf(s[3], SCALE_C, -n1));
  r0 = movm(pack2(p0, p1));
  r1 = movm(pack2(p2, p3));
  st.l0 = fmaf(st.l0, a0, p0 + p2);
  st.l1 = fmaf(st.l1, a1, p1 + p3);
#pragma unroll
  for (int i = 0; i < 4; i++) {
    st.o[i][0] *= a0; st.o[i][1] *= a1; st.o[i][2] *= a0; st.o[i][3] *= a1;
  }
}

__device__ __forceinline__ void tile_smem(Attn& st, uint32_t kaddr, uint32_t vaddr, uint32_t qaddr, bool lowg) {
  float s[4] = {0.f, 0.f, 0.f, 0.f}, s2[4] = {0.f, 0.f, 0.f, 0.f};
#pragma unroll
  for (int j = 0; j < 4; j++) {
    uint32_t q0, q1, q2, q3, a0, a1, a2, a3, c0, c1, c2, c3;
    ldsm4(q0, q1, q2, q3, qaddr + j * 64);
    ldsm4(a0, a1, a2, a3, (kaddr ^ (((2 * j) & 3) << 5)) + (j >> 1) * 2048);
    ldsm4(c0, c1, c2, c3, (kaddr ^ (((2 * j + 1) & 3) << 5)) + (j >> 1) * 2048);
    mma(s, a0, a1, a2, a3, q0, q1);
    mma(s2, c0, c1, c2, c3, q2, q3);
  }
#pragma unroll
  for (int i = 0; i < 4; i++) s[i] += s2[i];
  uint32_t r0, r1;
  softmax_step(st, s, r0, r1);
#pragma unroll
  for (int kg = 0; kg < 2; kg++) {
    uint32_t r = kg ? r1 : r0;
    uint32_t b0 = lowg ? r : 0u, b1 = lowg ? 0u : r;
#pragma unroll
    for (int mt = 0; mt < 4; mt++) {
      uint32_t a0, a1, a2, a3;
      ldsm4t(a0, a1, a2, a3, (vaddr ^ (mt << 5)) + kg * 1024);
      mma(st.o[mt], a0, a1, a2, a3, b0, b1);
    }
  }
}

__device__ __forceinline__ void lds128(uint32_t& a, uint32_t& b, uint32_t& c, uint32_t& d, uint32_t addr) {
  asm volatile("ld.shared.v4.u32 {%0,%1,%2,%3}, [%4];" : "=r"(a), "=r"(b), "=r"(c), "=r"(d) : "r"(addr) : "memory");
}
__device__ __forceinline__ void sts128(uint32_t addr, uint32_t a, uint32_t b, uint32_t c, uint32_t d) {
  asm volatile("st.shared.v4.u32 [%0], {%1,%2,%3,%4};" ::"r"(addr), "r"(a), "r"(b), "r"(c), "r"(d) : "memory");
}

constexpr uint32_t PK_M = 0x78007800u, PK_S = 0x80008000u;
constexpr int EXC_CAP = 25;

__device__ __forceinline__ uint32_t lds32(uint32_t addr) {
  uint32_t v;
  asm volatile("ld.shared.u32 %0, [%1];" : "=r"(v) : "r"(addr) : "memory");
  return v;
}

__device__ __forceinline__ bool pack_prepare(uint32_t img, int lane, int r, uint32_t& bases, uint32_t& exc, uint32_t& cnt) {
  bool ok = true;
  bases = 0;
  uint32_t c = cnt;
#pragma unroll 1
  for (int h = 0; h < 2; h++) {
    const uint32_t base = img + h * 4096 + lane * 16;
    uint32_t mx = 0u, mn = 0xffffffffu;
#pragma unroll
    for (int i = 0; i < 8; i++) {
      uint32_t w0, w1, w2, w3;
      lds128(w0, w1, w2, w3, base + i * 512);
      w0 &= ~PK_S; w1 &= ~PK_S; w2 &= ~PK_S; w3 &= ~PK_S;
      mx = __vimax3_u16x2(mx, w0, w1); mx = __vimax3_u16x2(mx, w2, w3);
      mn = __viaddmin_u16x2(w0, 0xffffffffu, mn); mn = __viaddmin_u16x2(w1, 0xffffffffu, mn);
      mn = __viaddmin_u16x2(w2, 0xffffffffu, mn); mn = __viaddmin_u16x2(w3, 0xffffffffu, mn);
    }
    const uint32_t e = __reduce_max_sync(0xffffffffu, max(mx & 0xffffu, mx >> 16)) >> 7;
    const uint32_t B = e > 15u ? e - 15u : 0u, thr = B << 7;
    bases |= B << (8 * h);
    uint32_t todo = __ballot_sync(0xffffffffu, min(mn & 0xffffu, mn >> 16) < thr);
    if (__popc(todo) > 8) ok = false;
    while (todo && ok) {
      const int src = __ffs(todo) - 1;
      todo &= todo - 1;
      const uint32_t off = h * 4096 + src * 16 + (lane >> 2) * 512 + (lane & 3) * 4;
      const uint32_t w = lds32(img + off);
#pragma unroll 1
      for (int j = 0; j < 2; j++) {
        const uint32_t v = j ? w >> 16 : w & 0xffffu;
        uint32_t m = __ballot_sync(0xffffffffu, (v & 0x7fffu) - 1u < thr);
        if (c + __popc(m) > EXC_CAP) { ok = false; break; }
        while (m) {
          const uint32_t en = __shfl_sync(0xffffffffu, (v << 16) | (r << 12) | ((off >> 1) + j), __ffs(m) - 1);
          m &= m - 1;
          if (lane == (int)c) exc = en;
          c++;
        }
      }
    }
  }
  if (ok) cnt = c;
  return ok;
}

__device__ __forceinline__ void pack4(uint32_t& p0, uint32_t& p1, uint32_t& p2, uint32_t w0, uint32_t w1, uint32_t w2,
                                      uint32_t w3, uint32_t nb) {
  const uint32_t x0 = __viaddmax_s16x2(w0 & ~PK_S, nb, 0u), x1 = __viaddmax_s16x2(w1 & ~PK_S, nb, 0u);
  const uint32_t x2 = __viaddmax_s16x2(w2 & ~PK_S, nb, 0u), x3 = __viaddmax_s16x2(w3 & ~PK_S, nb, 0u);
  p0 = x0 | (w0 & PK_S) | ((x3 << 11) & PK_M);
  p1 = x1 | (w1 & PK_S) | ((x3 << 7) & PK_M);
  p2 = x2 | (w2 & PK_S) | ((x3 << 3) & 0x38003800u) | ((w3 >> 1) & 0x40004000u);
}
__device__ __forceinline__ void unpack4_store(uint32_t addr, uint32_t p0, uint32_t p1, uint32_t p2, uint32_t thr) {
  const uint32_t x3 = ((p0 >> 11) & 0x000f000fu) | ((p1 >> 7) & 0x00f000f0u) | ((p2 >> 3) & 0x07000700u);
  sts128(addr, (p0 & ~PK_M) + __vminu2(p0 & 0x07ff07ffu, 0x00010001u) * thr,
         (p1 & ~PK_M) + __vminu2(p1 & 0x07ff07ffu, 0x00010001u) * thr,
         (p2 & ~PK_M) + __vminu2(p2 & 0x07ff07ffu, 0x00010001u) * thr,
         (x3 | ((p2 << 1) & PK_S)) + __vminu2(x3, 0x00010001u) * thr);
}
__device__ __forceinline__ uint32_t neg_base(uint32_t b) { return ((0u - (b << 7)) & 0xffffu) * 0x00010001u; }

__device__ __forceinline__ void grab_tile(uint32_t (&p)[48], uint32_t src) {
#pragma unroll
  for (int i = 0; i < 48; i++) p[i] = lds32(src + i * 128);
}
__device__ __forceinline__ void drop_tile(const uint32_t (&p)[48], uint32_t dst) {
#pragma unroll
  for (int i = 0; i < 48; i++) sts32(dst + i * 128, p[i]);
}
__device__ __forceinline__ void pack_tile_smem(uint32_t pk, uint32_t pv, uint32_t img, int lane, uint32_t bases) {
#pragma unroll 1
  for (int h = 0; h < 4; h++) {
    const uint32_t nb = neg_base((bases >> (8 * (h >> 1))) & 0xffu);
    const uint32_t src = img + h * 2048 + lane * 16, dst = ((h & 2) ? pv : pk) + (h & 1) * 1536 + lane * 4;
    uint32_t p[12];
#pragma unroll
    for (int i = 0; i < 4; i++) {
      uint32_t w0, w1, w2, w3;
      lds128(w0, w1, w2, w3, src + i * 512);
      pack4(p[3 * i], p[3 * i + 1], p[3 * i + 2], w0, w1, w2, w3, nb);
    }
    __syncwarp();
#pragma unroll
    for (int i = 0; i < 12; i++) sts32(dst + i * 128, p[i]);
  }
}
__device__ __forceinline__ void unpack_tile_smem(uint32_t pk, uint32_t pv, uint32_t img, int lane, uint32_t bases) {
#pragma unroll 1
  for (int h = 0; h < 4; h++) {
    const uint32_t thr = ((bases >> (8 * (h >> 1))) & 0xffu) << 7;
    const uint32_t dst = img + h * 2048 + lane * 16, src = ((h & 2) ? pv : pk) + (h & 1) * 1536 + lane * 4;
    uint32_t p[12];
#pragma unroll
    for (int i = 0; i < 12; i++) p[i] = lds32(src + i * 128);
    __syncwarp();
#pragma unroll
    for (int i = 0; i < 4; i++) unpack4_store(dst + i * 512, p[3 * i], p[3 * i + 1], p[3 * i + 2], thr);
  }
}

template <int H>
__device__ __forceinline__ void w_frags(uint32_t (&A)[32], uint32_t seg, int lane) {
  const int row = (lane & 7) + ((lane >> 4) << 3);
  const uint32_t base = seg + row * 64 + ((((lane >> 3) & 1) ^ ((row >> 1) & 3)) << 4);
#pragma unroll
  for (int i = 0; i < 4; i++)
    ldsm4t(A[16 * H + 4 * i], A[16 * H + 4 * i + 1], A[16 * H + 4 * i + 2], A[16 * H + 4 * i + 3],
           (base ^ ((i & 1) << 5)) + (i >> 1) * 1024);
}

template <int NKS, bool LN, int FMT>
__device__ __forceinline__ void gemv_regs(const uint32_t (&A)[32], uint32_t sb, int warp, int lane, uint32_t xw,
                                          uint32_t* dst, bool real) {
  float acc[2][4] = {{0.f, 0.f, 0.f, 0.f}, {0.f, 0.f, 0.f, 0.f}};
  const int t = lane & 3, g = lane >> 2;
  float s1 = lo16(xw) + hi16(xw), s2 = fmaf(lo16(xw), lo16(xw), hi16(xw) * hi16(xw));
#pragma unroll
  for (int ks = 0; ks < NKS; ks++) {
    const uint32_t x0 = __shfl_sync(0xffffffffu, xw, 8 * ks + t);
    const uint32_t x1 = __shfl_sync(0xffffffffu, xw, 8 * ks + 4 + t);
    const uint32_t b0 = (LN && (g & 1)) ? 0x3f803f80u : x0, b1 = (LN && (g & 1)) ? 0x3f803f80u : x1;
    mma(acc[0], A[8 * ks], A[8 * ks + 1], A[8 * ks + 2], A[8 * ks + 3], b0, b1);
    mma(acc[1], A[8 * ks + 4], A[8 * ks + 5], A[8 * ks + 6], A[8 * ks + 7], b0, b1);
    if (LN) {
      s1 += __shfl_xor_sync(0xffffffffu, s1, 16 >> ks);
      s2 += __shfl_xor_sync(0xffffffffu, s2, 16 >> ks);
    }
  }
  if (LN) {
    s1 += __shfl_xor_sync(0xffffffffu, s1, 1);
    s2 += __shfl_xor_sync(0xffffffffu, s2, 1);
  }
  const float v = (t & 2) ? ((t & 1) ? acc[1][2] : acc[1][0]) : ((t & 1) ? acc[0][2] : acc[0][0]);
  if (LN) {
    const float cs = (t & 2) ? ((t & 1) ? acc[1][3] : acc[1][1]) : ((t & 1) ? acc[0][3] : acc[0][1]);
    stsf2(sb + SM_Q + (warp * 32 + 8 * t + g) * 8, v, cs);
    if (lane == 0) stsf2(sb + SM_STAT + warp * 8, s2, s1);
  } else {
    stsf(sb + SM_Q + (warp * 32 + 8 * t + g) * 4, v);
  }
  dst = pin(dst);
  uint32_t ra = sb + SM_Q + lane * (LN ? 8 : 4);
  asm volatile("" : "+r"(ra));
  __syncthreads();
  if (warp == 0) {
    float y;
    if (LN) {
      float u[8], c[8], q[8], m[8];
#pragma unroll
      for (int w = 0; w < 8; w++) ldsf2(q[w], m[w], sb + SM_STAT + w * 8);
#pragma unroll
      for (int w = 0; w < 8; w++) ldsf2(u[w], c[w], ra + w * 256);
      const float mean = (((m[0] + m[1]) + (m[2] + m[3])) + ((m[4] + m[5]) + (m[6] + m[7]))) * (1.f / 512.f);
      const float msq = (((q[0] + q[1]) + (q[2] + q[3])) + ((q[4] + q[5]) + (q[6] + q[7]))) * (1.f / 512.f);
      const float vb = rbf(fmaxf(fmaf(-mean, mean, msq), 0.f));
      float sq, rs;
      asm("sqrt.approx.ftz.f32 %0, %1;" : "=f"(sq) : "f"(rbf(vb + 1e-5f)));
      asm("rcp.approx.ftz.f32 %0, %1;" : "=f"(rs) : "f"(rbf(sq)));
      y = ((u[0] + u[1]) + (u[2] + u[3])) + ((u[4] + u[5]) + (u[6] + u[7]));
      const float cs = ((c[0] + c[1]) + (c[2] + c[3])) + ((c[4] + c[5]) + (c[6] + c[7]));
      y = fmaf(-rbf(mean), cs, y) * rs;
    } else {
      float u[8];
#pragma unroll
      for (int w = 0; w < 8; w++) u[w] = ldsf(ra + w * 128);
      y = ((u[0] + u[1]) + (u[2] + u[3])) + ((u[4] + u[5]) + (u[6] + u[7]));
    }
    uint32_t o;
    if (FMT == 2) o = pack2(y, __shfl_down_sync(0xffffffffu, y, 1));
    else o = __float_as_uint(FMT == 1 ? rbf(y) : y);
    o = enc(o);
    asm volatile("{.reg .pred p; setp.ne.u32 p, %2, 0; @p st.relaxed.gpu.global.u32 [%0], %1;}"
                 ::"l"(dst), "r"(o), "r"((uint32_t)(real && (FMT != 2 || !(lane & 1)))) : "memory");
  }
}

template <int NP, class F, class G>
__device__ __forceinline__ uint32_t add_partials(const uint32_t* p, uint32_t xw, bool real, F side, G after) {
  uint32_t a[NP], b[NP];
#pragma unroll
  for (int k = 0; k < NP; k++) a[k] = b[k] = 0u;
  int it = 0;
  bool pend, done = false;
  if (real) do {
#pragma unroll
    for (int k = 0; k < NP; k++)
      if (a[k] == 0u || b[k] == 0u) ldr64(a[k], b[k], p + k * 512);
    if (!done) done = side();
    const uint32_t m0 = __vimin3_u32(__vimin3_u32(a[0], b[0], a[1]), __vimin3_u32(b[1], a[2], b[2]), __vimin3_u32(a[3], b[3], a[4]));
    const uint32_t m1 = __vimin3_u32(__vimin3_u32(b[4], a[5], b[5]), __vimin3_u32(a[6], b[6], a[NP - 1]), b[NP - 1]);
    pend = min(m0, m1) == 0u;
    if (!done) done = side();
    if (++it > SPIN_LIMIT) __trap();
  } while (__any_sync(0xffffffffu, pend) || !done);
  auto f = [](uint32_t u) { return __uint_as_float(u); };
  float y0 = ((f(a[0]) + f(a[1])) + (f(a[2]) + f(a[3]))) + ((f(a[4]) + f(a[5])) + (NP == 8 ? f(a[6]) + f(a[NP - 1]) : f(a[6])));
  float y1 = ((f(b[0]) + f(b[1])) + (f(b[2]) + f(b[3]))) + ((f(b[4]) + f(b[5])) + (NP == 8 ? f(b[6]) + f(b[NP - 1]) : f(b[6])));
  asm volatile("" : "+f"(y0), "+f"(y1));
  after();
  return pack2(lo16(xw) + rbf(y0), hi16(xw) + rbf(y1));
}

__global__ void __launch_bounds__(NTHR, 1)
decode_kernel(const __grid_constant__ Maps maps, const uint32_t* __restrict__ x_in,
              const char* __restrict__ Kp, const char* __restrict__ Vp, uint32_t* __restrict__ out, int r1, int r2, int r4) {
  extern __shared__ __align__(1024) unsigned char smem[];
  const uint32_t sb = (uint32_t)__cvta_generic_to_shared(smem);
  const int tid = threadIdx.x, lane = tid & 31;
  const int warp = __shfl_sync(0xffffffffu, tid >> 5, 0);
  const int cta = blockIdx.x;
  const int head_lo = cta < 128 ? ((cta + 3 * (cta >> 3)) & 7) : 2 * (cta - 128), head_hi = cta < 128 ? head_lo : head_lo + 1;
  const int head = warp < 4 ? head_lo : head_hi;
  const int rot = ((head & 1) ? r1 : 0) + ((head & 2) ? r2 : 0) + ((head & 4) ? r4 : 0);
  const int jw = cta < 128 ? (cta >> 3) * 8 + warp : 128 + (warp & 3);
  const uint32_t ring = sb + warp * WARP_BYTES;
  const uint32_t rbar = sb + SM_BAR + warp * 40;
  const uint32_t wbar = rbar + 24;
  const uint32_t wseg = ring + O_W;

  auto w_issue = [&](int half, const CUtensorMap* m, int col, int row) {
    if (lane == 0) {
      mbar_expect(wbar + half * 8, 2048);
      tma2d(wseg + half * 2048, m, col, row, wbar + half * 8, pol_evict_first());
    }
    __syncwarp();
  };
  auto issue_demote = [&](int sl, int t) {
    if (lane == 0) {
      uint64_t pn;
      asm volatile("createpolicy.fractional.L2::evict_normal.b64 %0, 1.0;" : "=l"(pn));
      const uint64_t pf = pol_evict_first();
      const int row = head * SK + ((t + rot) & 4095) * 16;
      const uint32_t dst = ring + sl * SLOT_BYTES, b = rbar + sl * 8;
      mbar_expect(b, SLOT_BYTES);
      tma3d(dst, &maps.k, row, b, pn);
      asm volatile("cp.async.bulk.prefetch.L2.global.L2::cache_hint [%0], %1, %2;" ::"l"(Kp + (size_t)row * 256), "r"(4096), "l"(pf) : "memory");
      tma3d(dst + 4096, &maps.v, row, b, pn);
      asm volatile("cp.async.bulk.prefetch.L2.global.L2::cache_hint [%0], %1, %2;" ::"l"(Vp + (size_t)row * 256), "r"(4096), "l"(pf) : "memory");
    }
    __syncwarp();
  };
  auto issue = [&](int sl, int t, bool kp) {
    if (lane == 0) {
      const uint64_t pf = pol_evict_first();
      const int row = head * SK + ((t + rot) & 4095) * 16;
      const uint32_t dst = ring + sl * SLOT_BYTES, b = rbar + sl * 8;
      mbar_expect(b, SLOT_BYTES);
      tma3d(dst, &maps.k, row, b, pf);
      if (kp) l2_prefetch(Kp + (size_t)row * 256, 4096);
      tma3d(dst + 4096, &maps.v, row, b, pf);
      if (kp) l2_prefetch(Vp + (size_t)row * 256, 4096);
    }
    __syncwarp();
  };
  auto stack_tile = [&](uint32_t r) -> int { return r == 5 ? 6 * WPH + (jw >> 1) : jw + (r == 6 ? 5 : (int)r) * WPH; };

  uint32_t xw = __ldg(x_in + tid);
  if (lane == 0) {
    if (sb & 1023) __trap();
#pragma unroll
    for (int i = 0; i < 5; i++) mbar_init(rbar + i * 8, 1);
    asm volatile("fence.mbarrier_init.release.cluster;" ::: "memory");
    fence_async();
  }
  if (cta < 128) { w_issue(0, &maps.wq, cta * 32, warp * 64); w_issue(1, &maps.wq, cta * 32, warp * 64 + 32); }
  if (tid == 0 && cta < 128 && (cta & 15) == 0) {
    g_s.ctr[0][cta >> 4][0] = 0;
    asm volatile("fence.acq_rel.gpu;" ::: "memory");
  }
  __syncwarp();
  issue_demote(2, jw);
  if (tid == 32) {
    asm volatile("prefetch.tensormap [%0];" ::"l"(&maps.wo) : "memory");
    asm volatile("prefetch.tensormap [%0];" ::"l"(&maps.wg) : "memory");
    asm volatile("prefetch.tensormap [%0];" ::"l"(&maps.wu) : "memory");
    asm volatile("prefetch.tensormap [%0];" ::"l"(&maps.wd) : "memory");
  }
  __syncwarp();

  uint32_t c0[48], c1[48], c2[48], c3[48];
#pragma unroll
  for (int i = 0; i < 48; i++) { c0[i] = 0; c1[i] = 0; c2[i] = 0; c3[i] = 0; }
  uint32_t exc = 0;

  uint32_t sst = 0;

  for (int layer = -1; layer < 2; layer++) {
    const bool live = layer >= 0;
    const int ly = live ? layer : 0;

    if (live) {
      Attn st;
#pragma unroll
      for (int i = 0; i < 4; i++) { st.o[i][0] = st.o[i][1] = st.o[i][2] = st.o[i][3] = 0.f; }
      st.m0 = st.m1 = -INFINITY; st.l0 = st.l1 = 0.f;
      const int ln = fresh_lane();
      const uint32_t koff = ((ln & 7) + ((ln >> 3) & 1) * 8) * 128 + (((ln >> 4) ^ (ln & 7)) << 4);
      const uint32_t voff = 4096 + (ln >> 4) * 2048 + (ln & 7) * 128 + ((((ln >> 3) & 1) ^ (ln & 7)) << 4);
      const uint32_t qaddr = sb + SM_Q + ((head - head_lo) * 4 + (ln & 3)) * Q_PITCH + (ln >> 3) * 16;
      const bool lowg = ln < 16;
      int nxt = jw - NSTAT * WPH;
      if (layer == 0) { sst = 7; nxt += WPH; }
      else sst = ((sst ^ 0x10) & 0x3ff0770) | 1;
      while (true) {
        int sl = -1;
        if ((sst & 2) && mbar_test(rbar + 8, (sst >> 5) & 1)) sl = 1;
        if (sst & 4) sl = 2;
        if ((sst & 1) && mbar_test(rbar, (sst >> 4) & 1)) sl = 0;
        sl = __shfl_sync(0xffffffffu, sl, 0);
        if (sl >= 0) {
          tile_smem(st, ring + sl * SLOT_BYTES + koff, ring + sl * SLOT_BYTES + voff, qaddr, lowg);
          __syncwarp();
          sst ^= 0x11u << sl;
          if (sl == 0) sst |= 0x2000;
          if (layer == 0) {
            if (sl != 0 || (sst & 0x8000)) {
              const int l_ = fresh_lane();
              const uint32_t r = (sst >> 8) & 7, img = ring + sl * SLOT_BYTES;
              uint32_t bases, cnt = (sst >> 21) & 31;
              if (!pack_prepare(img, l_, r, bases, exc, cnt)) bases |= 0x10000;
              sst = ((sst & ~(31u << 21) & ~0x8000u) | (cnt << 21)) + ((r == 4 && (warp & 1)) ? 0x200 : 0x100);
              if (l_ == EXC_CAP + (int)r) exc = bases;
              const uint32_t pk = r < 4 ? img : ring + (r == 4 ? O_C1 : r == 5 ? O_E : O_C0);
              pack_tile_smem(pk, pk + (r == 5 ? WARP_BYTES : 3072), img, l_, bases);
              if (r == 0) grab_tile(c0, img + l_ * 4);
              else if (r == 1) grab_tile(c1, img + l_ * 4);
              else if (r == 2) grab_tile(c2, img + l_ * 4);
              else if (r == 3) grab_tile(c3, img + l_ * 4);
              fence_async();
              __syncwarp();
              if (sl == 1 && (sst & 0x700) < 0x600) { issue(1, stack_tile((sst >> 8) & 7), false); sst |= 2; }
            }
          } else if (sl == 1 && ((sst >> 16) & 31)) {
            sst -= 1u << 16;
            uint32_t t;
            asm volatile("ld.shared.u16 %0, [%1];" : "=r"(t) : "r"(sb + SM_LIST + warp * (KCAP * 2) + ((sst >> 16) & 31) * 2) : "memory");
            issue(1, t, false); sst |= 2;
          }
        } else if (layer == 1 && (sst & 0x700) && !(sst & 2) && ((sst & 0x2000) || !(sst & 1))) {
          const int l_ = fresh_lane();
          const uint32_t r = ((sst >> 8) & 7) - 1, img = ring + SLOT_BYTES;
          sst = ((sst - ((r == 6 && (warp & 1)) ? 0x200 : 0x100)) | 2) & ~0x2000u;
          const uint32_t hdr = __shfl_sync(0xffffffffu, exc, EXC_CAP + r);
          if (hdr & 0x10000) {
            issue(1, stack_tile(r), false);
          } else {
            const uint32_t pk = ring + (r <= 4 ? O_C1 : r == 5 ? O_E : O_C0);
            if (r == 0) drop_tile(c0, pk + l_ * 4);
            else if (r == 1) drop_tile(c1, pk + l_ * 4);
            else if (r == 2) drop_tile(c2, pk + l_ * 4);
            else if (r == 3) drop_tile(c3, pk + l_ * 4);
            unpack_tile_smem(pk, pk + (r == 5 ? WARP_BYTES : 3072), img, l_, hdr);
            __syncwarp();
            if (l_ < (int)((sst >> 21) & 31) && ((exc >> 12) & 7) == r)
              asm volatile("st.shared.u16 [%0], %1;" ::"r"(img + (exc & 0xfffu) * 2), "r"(exc >> 16) : "memory");
            fence_async();
            __syncwarp();
            if (l_ == 0) mbar_expect(rbar + 8, 0);
          }
          __syncwarp();
        } else if (warp == 7 && (sst & 0x88) == 8) {
          sst = (sst | 0x80) & ~0x2000u;
          const int l_ = fresh_lane(), c_ = opaque(cta), y_ = opaque(ly);
          const uint4 z = make_uint4(0, 0, 0, 0);
          const int s_lo = c_ >> 3;
          uint4* po = reinterpret_cast<uint4*>(&g_s.PO[y_][head_lo][s_lo][0]);
          po[l_] = z; po[l_ + 32] = z;
          if (l_ < 2) reinterpret_cast<uint4*>(&g_s.ML[y_][head_lo][s_lo][0])[l_] = z;
          if (head_hi != head_lo) {
            po = reinterpret_cast<uint4*>(&g_s.PO[y_][head_hi][16][0]);
            po[l_] = z; po[l_ + 32] = z;
            if (l_ < 2) reinterpret_cast<uint4*>(&g_s.ML[y_][head_hi][16][0])[l_] = z;
          }
          if (c_ < 128) {
            (&g_s.Y1[y_][0][0])[c_ * 32 + l_] = 0;
            if (y_ == 0 && l_ < 16) g_s.QX[1][c_ * 16 + l_] = 0;
          }
          if (c_ < 112) { g_s.GU[y_][c_ * 32 + l_] = 0; (&g_s.Y2[y_][0][0])[c_ * 32 + l_] = 0; }
          if (c_ < 8 && y_ == 0 && l_ == 0) g_s.ctr[1][c_][0] = 0;
          __syncwarp();
          if (l_ == 0) {
            asm volatile("fence.acq_rel.gpu;" ::: "memory");
            const uint32_t old = atomicAdd(&g_s.cnt[y_][0], 1u);
            sts32(sb + SM_STAT + 64, (old / NCTA + 1) * NCTA);
          }
          __syncwarp();
        } else if ((sst & 7) == 0) {
          break;
        } else if ((sst & 0x3080) == 0x2080) {
          uint32_t target, c;
          asm volatile("ld.shared.u32 %0, [%1];" : "=r"(target) : "r"(sb + SM_STAT + 64) : "memory");
          asm volatile("ld.acquire.gpu.global.u32 %0, [%1];" : "=r"(c) : "l"(&g_s.cnt[opaque(ly)][0]) : "memory");
          sst &= ~0x2000u;
          if (__all_sync(0xffffffffu, (int)(c - target) >= 0)) sst |= 0x1000;
        } else {
          int it = 0;
          while (!__any_sync(0xffffffffu, ((sst & 1) && mbar_test(rbar, (sst >> 4) & 1)) || ((sst & 2) && mbar_test(rbar + 8, (sst >> 5) & 1))))
            if (++it > (SPIN_LIMIT << 3)) __trap();
        }
        if (!(sst & 0x801) && !(layer == 1 && (warp & 3) == 0 && (sst & 0x700))) {
          if (layer == 0 && (sst & 0x700) == 0x600) {
            issue(0, stack_tile(6), false); sst |= 0x8001;
          } else {
            const int d = __shfl_sync(0xffffffffu, nxt, 8) + NSTAT * WPH;
            const int nd = layer == 0 ? N_ALL : N_DYN;
            if (d >= nd - RESET_X) sst |= 8;
            if (d < nd) {
              const bool kp = d >= N_DYN;
              issue(0, T_DYN + d, kp); sst |= 1;
              if (kp) {
                if (lane == 0)
                  asm volatile("st.shared.u16 [%0], %1;" ::"r"(sb + SM_LIST + warp * (KCAP * 2) + ((sst >> 16) & 31) * 2), "r"(T_DYN + d) : "memory");
                sst += 1u << 16;
              }
              const bool full = (layer == 0 && ((sst >> 16) & 31) == KCAP) || ((warp & 3) == 0 && d >= nd - STOP_X), stat = d < (NSTAT - 1) * WPH;
              nxt = full ? 1 << 20 : d - (NSTAT - 1) * WPH;
              if (layer == 0 && !stat && d < NSTAT * WPH) {
                asm volatile("{.reg .u32 t; ld.acquire.gpu.global.u32 t, [%0];}" ::"l"(&g_s.QX[0][head * 256]) : "memory");
              }
              asm volatile("{.reg .pred p; setp.ne.u32 p, %2, 0; @p atom.global.relaxed.gpu.inc.u32 %0, [%1], 0x7fffffff;}"
                           : "+r"(nxt) : "l"(&g_s.ctr[layer][head][0]), "r"((uint32_t)(lane == 8 && !full && !stat)) : "memory");
              __syncwarp();
            } else if (layer == 1) {
              sst |= 0x800;
            } else if ((sst & 0x700) == 0x700) {
              issue(0, T_LAST + jw, false); sst |= 0x801;
            }
          }
        }
      }
      int rank = __shfl_sync(0xffffffffu, nxt, 8) + NSTAT * WPH - (layer == 0 ? N_ALL : N_DYN);

      {
#pragma unroll
        for (int o = 4; o <= 16; o <<= 1) {
          st.l0 += __shfl_xor_sync(0xffffffffu, st.l0, o);
          st.l1 += __shfl_xor_sync(0xffffffffu, st.l1, o);
        }
        const int g = lane >> 2, t = lane & 3;
        const uint32_t a = ring + O_P + ((t & 1) * 128 + (t >> 1) * 64) * 4;
#pragma unroll
        for (int mt = 0; mt < 4; mt++) {
          sts32(a + ((16 * mt + g) ^ (8 * t)) * 4, pack2(st.o[mt][0], st.o[mt][1]));
          sts32(a + ((16 * mt + 8 + g) ^ (8 * t)) * 4, pack2(st.o[mt][2], st.o[mt][3]));
        }
        if (lane < 2)
          sts128(sb + SM_ML + warp * 32 + lane * 16, __float_as_uint(st.m0), __float_as_uint(st.l0),
                 __float_as_uint(st.m1), __float_as_uint(st.l1));
      }
      {
        const int hp = tid >> 7, d = tid & 127, odd = tid & 1, hq = 2 * hp + odd;
        uint32_t* ppo = pin(&g_s.PO[ly][head_lo][cta >> 3][hq * 64 + (d >> 1)]);
        uint32_t* pml = pin(&g_s.ML[ly][head_lo][cta >> 3][2 * hq]);
        uint32_t am = sb + SM_ML + hp * 16 + odd * 8;
        uint32_t ap = sb + O_P + (hp * 128 + ((d & ~1) ^ (8 * (hp + 2 * (d >> 6))))) * 4;
        uint32_t sel = odd ? 0x7632 : 0x5410;
        asm volatile("" : "+r"(am), "+r"(ap), "+r"(sel));
        if (cta < 128) {
          if (rank > 100000) rank = STOP_R;
          if (rank < WO_R0) {
            const uint32_t c0_ = clock();
            while (__any_sync(0xffffffffu, (uint32_t)clock() - c0_ < (uint32_t)((WO_R0 - rank) * WO_K))) {}
          }
          w_issue(0, &maps.wo, (cta & 15) * 32, (cta >> 4) * 512 + warp * 64);
        }
        __syncthreads();
        float mw[8], lw[8];
        uint32_t u[8];
#pragma unroll
        for (int w = 0; w < 8; w++) ldsf2(mw[w], lw[w], am + w * 32);
#pragma unroll
        for (int w = 0; w < 8; w++) {
          uint32_t x0, x1;
          asm volatile("ld.shared.v2.u32 {%0,%1}, [%2];" : "=r"(x0), "=r"(x1) : "r"(ap + w * WARP_BYTES) : "memory");
          u[w] = __byte_perm(x0, x1, sel);
        }
        const bool split = head_hi != head_lo;
        float Ma = fmaxf(fmaxf(mw[0], mw[1]), fmaxf(mw[2], mw[3]));
        float Mb = fmaxf(fmaxf(mw[4], mw[5]), fmaxf(mw[6], mw[7]));
        if (!split) Ma = Mb = fmaxf(Ma, Mb);
        float La = 0.f, a0 = 0.f, a1 = 0.f, Lb = 0.f, b0 = 0.f, b1 = 0.f;
#pragma unroll
        for (int w = 0; w < 4; w++) {
          const float ea = ex2(mw[w] - Ma), eb = ex2(mw[w + 4] - Mb);
          La = fmaf(lw[w], ea, La); a0 = fmaf(lo16(u[w]), ea, a0); a1 = fmaf(hi16(u[w]), ea, a1);
          Lb = fmaf(lw[w + 4], eb, Lb); b0 = fmaf(lo16(u[w + 4]), eb, b0); b1 = fmaf(hi16(u[w + 4]), eb, b1);
        }
        if (!split) { La += Lb; a0 += b0; a1 += b1; }
        if (d < 2) str64(pml, enc(__float_as_uint(Ma)), enc(__float_as_uint(La)));
        const float ia = rcp(La);
        str32(ppo, enc(pack2(a0 * ia, a1 * ia)));
        if (split) {
          if (d < 2) str64(pml + 17 * 8, enc(__float_as_uint(Mb)), enc(__float_as_uint(Lb)));
          const float ib = rcp(Lb);
          str32(ppo + 17 * 256, enc(pack2(b0 * ib, b1 * ib)));
        }
      }
      if (cta < 128) w_issue(1, &maps.wo, (cta & 15) * 32, (cta >> 4) * 512 + warp * 64 + 32);
      if (tid == 255 && !(sst & 0x1000)) {
        uint32_t target, c;
        asm volatile("ld.shared.u32 %0, [%1];" : "=r"(target) : "r"(sb + SM_STAT + 64) : "memory");
        int it = 0;
        do {
          asm volatile("ld.acquire.gpu.global.u32 %0, [%1];" : "=r"(c) : "l"(&g_s.cnt[ly][0]) : "memory");
          if (++it > SPIN_LIMIT) __trap();
        } while ((int)(c - target) < 0);
      }
      __syncwarp();
      __syncthreads();
    }

    if (cta < 128) {
      uint32_t A[32];
      if (live) {
#pragma unroll 1
        for (int real = 0; real < 2; real++) {
#pragma unroll
          for (int i = 0; i < 16; i++) A[i] = 0u;
          const int rb = cta >> 4;
          const uint32_t* pp = pin(&g_s.PO[ly][rb][0][tid]);
          const uint32_t* pm = pin(&g_s.ML[ly][rb][lane < 17 ? lane : 0][2 * (warp >> 1)]);
          uint32_t v[17], um = 0u, ul = 0u;
#pragma unroll
          for (int s = 0; s < 17; s++) v[s] = 0u;
          int it = 0;
          bool pend, done = false;
          if (real) {
            do {
              if (um == 0u || ul == 0u) ldr64(um, ul, pm);
#pragma unroll
              for (int s = 0; s < 17; s++)
                if (v[s] == 0u) v[s] = ldr32(pp + s * 256);
              if (!done && __all_sync(0xffffffffu, mbar_test(wbar, 1))) {
                w_frags<0>(A, wseg, lane);
                __syncwarp();
                if (cta < 112) w_issue(0, cta < 56 ? &maps.wg : &maps.wu, (cta < 56 ? cta : cta - 56) * 32, warp * 64);
                else if (layer == 0) w_issue(0, &maps.wq, cta * 32, warp * 64);
                done = true;
              }
              pend = __vimin3_u32(__vimin3_u32(__vimin3_u32(um, ul, v[0]), __vimin3_u32(v[1], v[2], v[3]), __vimin3_u32(v[4], v[5], v[6])),
                                  __vimin3_u32(__vimin3_u32(v[7], v[8], v[9]), __vimin3_u32(v[10], v[11], v[12]), __vimin3_u32(v[13], v[14], v[15])), v[16]) == 0u;
              if (++it > SPIN_LIMIT) __trap();
            } while (__any_sync(0xffffffffu, pend) || !done);
          }
          const float ms = __uint_as_float(um);
          int mi = __float_as_int(ms);
          mi = __reduce_max_sync(0xffffffffu, mi ^ ((mi >> 31) & 0x7fffffff));
          const float M = __int_as_float(mi ^ ((mi >> 31) & 0x7fffffff));
          const float e = lane < 17 ? __uint_as_float(ul) * ex2(ms - M) : 0.f;
          float L = 0.f, o0 = 0.f, o1 = 0.f, Lb = 0.f, p0 = 0.f, p1 = 0.f;
#pragma unroll
          for (int s = 0; s < 17; s++) {
            const float es = __shfl_sync(0xffffffffu, e, s);
            if (s & 1) { Lb += es; p0 = fmaf(es, lo16(v[s]), p0); p1 = fmaf(es, hi16(v[s]), p1); }
            else { L += es; o0 = fmaf(es, lo16(v[s]), o0); o1 = fmaf(es, hi16(v[s]), o1); }
          }
          o0 += p0; o1 += p1;
          asm volatile("" : "+f"(o0), "+f"(o1));
          if (real) mbar_wait(wbar + 8, cta < 112 ? layer ^ 1 : 1);
          w_frags<1>(A, wseg + 2048, lane);
          const float inv = rcp(L + Lb);
          gemv_regs<4, false, 0>(A, sb, warp, lane, pack2(o0 * inv, o1 * inv), &g_s.Y1[ly][0][0] + cta * 32 + lane, real);
          if (real) {
            if (cta < 112) w_issue(1, cta < 56 ? &maps.wg : &maps.wu, (cta < 56 ? cta : cta - 56) * 32, warp * 64 + 32);
            else if (layer == 0) w_issue(1, &maps.wq, cta * 32, warp * 64 + 32);
          }
          __syncthreads();
        }
#pragma unroll 1
        for (int real = 0; real < 2; real++) {
#pragma unroll
          for (int i = 0; i < 16; i++) A[i] = 0u;
          const uint32_t xn = add_partials<8>(pin(&g_s.Y1[ly][0][2 * tid]), xw, real, [&]() {
            if (cta >= 112) return true;
            if (!__all_sync(0xffffffffu, mbar_test(wbar, 0))) return false;
            w_frags<0>(A, wseg, lane);
            __syncwarp();
            w_issue(0, &maps.wd, (cta & 15) * 32, (cta >> 4) * 256 + warp * 32);
            return true;
          }, [&]() { if (real && cta < 112) mbar_wait(wbar + 8, layer); w_frags<1>(A, wseg + 2048, lane); });
          if (real) { xw = xn; }
          if (cta < 112) {
            gemv_regs<4, true, 1>(A, sb, warp, lane, xn, &g_s.GU[ly][cta * 32 + lane], real);
            if (real) {
              if (layer == 0) {
                w_issue(1, &maps.wq, cta * 32, warp * 64 + 32);
              }
            }
            __syncthreads();
          }
        }
        if (cta < 112) {
#pragma unroll 1
          for (int real = 0; real < 2; real++) {
#pragma unroll
            for (int i = 0; i < 16; i++) A[i] = 0u;
            const uint32_t* pg = pin(&g_s.GU[ly][(lane >> 4) * FF + (cta >> 4) * 256 + warp * 32 + (lane & 15) * 2]);
            uint32_t a = 0u, b = 0u;
            int it = 0;
            bool done = false;
            if (real) {
              do {
                if (a == 0u || b == 0u) ldr64(a, b, pg);
                if (!done && __all_sync(0xffffffffu, mbar_test(wbar, 1))) {
                  w_frags<0>(A, wseg, lane);
                  __syncwarp();
                  if (layer == 0) { w_issue(0, &maps.wq, cta * 32, warp * 64); }
                  done = true;
                }
                if (++it > SPIN_LIMIT) __trap();
              } while (__any_sync(0xffffffffu, a == 0u || b == 0u) || !done);
            }
            const float a0 = __uint_as_float(a), a1 = __uint_as_float(b);
            const float c0_ = __shfl_xor_sync(0xffffffffu, a0, 16), c1_ = __shfl_xor_sync(0xffffffffu, a1, 16);
            const float g0 = lane < 16 ? a0 : c0_, g1 = lane < 16 ? a1 : c1_;
            const float u0 = lane < 16 ? c0_ : a0, u1 = lane < 16 ? c1_ : a1;
            const uint32_t hw = pack2((g0 > 0.f ? g0 : g0 * 0.f) * u0, (g1 > 0.f ? g1 : g1 * 0.f) * u1);
            gemv_regs<2, false, 0>(A, sb, warp, lane, hw, &g_s.Y2[ly][0][0] + cta * 32 + lane, real);
            __syncthreads();
          }
        }
        if (layer == 1 && cta != 127) break;
        if (layer == 0 && warp == 4) {
          if (lane < 16) g_s.QX[0][cta * 16 + lane] = 0;
          __syncwarp();
        }
      }
#pragma unroll 1
      for (int real = live ? 0 : 1; real < 2; real++) {
#pragma unroll
        for (int i = 0; i < 16; i++) A[i] = 0u;
        if (!live) {
          mbar_wait(wbar, 0); mbar_wait(wbar + 8, 0);
          w_frags<0>(A, wseg, lane);
        }
        const uint32_t xn = add_partials<7>(pin(&g_s.Y2[ly][0][2 * tid]), xw, real && live, [&]() {
          if (layer == 1) return true;
          if (!__all_sync(0xffffffffu, mbar_test(wbar, 0) && mbar_test(wbar + 8, cta < 112 ? 1 : 0))) return false;
          w_frags<0>(A, wseg, lane);
          return true;
        }, [&]() { w_frags<1>(A, wseg + 2048, lane); });
        if (real && live) {
          xw = xn;
          if (layer == 1) { out[tid] = xn; return; }
        }
        gemv_regs<4, true, 2>(A, sb, warp, lane, xw, &g_s.QX[(layer + 1) & 1][cta * 16 + (lane >> 1)], real);
        if (!real) __syncthreads();
      }
    } else if (layer == 1) {
      break;
    }
    if (!live) {
      mbar_wait(rbar + 16, 0);
      issue_demote(1, jw + WPH);
    }
    __syncthreads();
    {
      const uint32_t* pq = &g_s.QX[layer + 1][head_lo * 256 + tid];
      uint32_t qv0 = 0u, qv1 = head_hi != head_lo ? 0u : 1u;
      int it = 0;
      do {
        if (qv0 == 0u) qv0 = ldr32(pq);
        if (qv1 == 0u) qv1 = ldr32(pq + 256);
        if (++it > SPIN_LIMIT) __trap();
      } while (__any_sync(0xffffffffu, qv0 == 0u || qv1 == 0u));
      if (!live) issue_demote(0, T_DYN + jw);
      sts32(sb + SM_Q + (tid >> 6) * Q_PITCH + (tid & 63) * 4, qv0);
      sts32(sb + SM_Q + (4 + (tid >> 6)) * Q_PITCH + (tid & 63) * 4, qv1);
    }
    __syncthreads();
  }
}

typedef CUresult (*EncodeFn)(CUtensorMap*, CUtensorMapDataType, cuuint32_t, void*, const cuuint64_t*,
                             const cuuint64_t*, const cuuint32_t*, const cuuint32_t*, CUtensorMapInterleave,
                             CUtensorMapSwizzle, CUtensorMapL2promotion, CUtensorMapFloatOOBfill);

void make_kv_map(EncodeFn enc, CUtensorMap* m, void* p) {
  cuuint64_t dims[3] = {64, (cuuint64_t)8 * SK, 2};
  cuuint64_t strides[2] = {256, 128};
  cuuint32_t box[3] = {64, 16, 2}, es[3] = {1, 1, 1};
  enc(m, CU_TENSOR_MAP_DATA_TYPE_BFLOAT16, 3, p, dims, strides, box, es, CU_TENSOR_MAP_INTERLEAVE_NONE,
      CU_TENSOR_MAP_SWIZZLE_128B, CU_TENSOR_MAP_L2_PROMOTION_NONE, CU_TENSOR_MAP_FLOAT_OOB_FILL_NONE);
}
void make_w_map(EncodeFn enc, CUtensorMap* m, void* p, int rows, int cols) {
  cuuint64_t dims[2] = {(cuuint64_t)cols, (cuuint64_t)rows};
  cuuint64_t strides[1] = {(cuuint64_t)cols * 2};
  cuuint32_t box[2] = {32, 32}, es[2] = {1, 1};
  enc(m, CU_TENSOR_MAP_DATA_TYPE_BFLOAT16, 2, p, dims, strides, box, es, CU_TENSOR_MAP_INTERLEAVE_NONE,
      CU_TENSOR_MAP_SWIZZLE_64B, CU_TENSOR_MAP_L2_PROMOTION_NONE, CU_TENSOR_MAP_FLOAT_OOB_FILL_NONE);
}

}

extern "C" void kernel_launch(void* const* d_in, const int* in_sizes, int n_in, void* d_out, int out_size) {
  (void)in_sizes; (void)n_in; (void)out_size;
  void* fn = nullptr;
  cudaDriverEntryPointQueryResult qr;
  cudaGetDriverEntryPoint("cuTensorMapEncodeTiled", &fn, cudaEnableDefault, &qr);
  EncodeFn enc = (EncodeFn)fn;
  Maps maps;
  make_kv_map(enc, &maps.k, d_in[1]);
  make_kv_map(enc, &maps.v, d_in[2]);
  make_w_map(enc, &maps.wq, d_in[3], DM, 4096);
  make_w_map(enc, &maps.wo, d_in[4], 4096, DM);
  make_w_map(enc, &maps.wg, d_in[6], DM, FF);
  make_w_map(enc, &maps.wu, d_in[7], DM, FF);
  make_w_map(enc, &maps.wd, d_in[8], FF, DM);
  cudaFuncSetAttribute(decode_kernel, cudaFuncAttributeMaxDynamicSharedMemorySize, SM_TOTAL);
  decode_kernel<<<NCTA, NTHR, SM_TOTAL, cudaStreamPerThread>>>(
      maps, (const uint32_t*)d_in[0], (const char*)d_in[1], (const char*)d_in[2], (uint32_t*)d_out, getenv("R1") ? atoi(getenv("R1")) : 0, getenv("R2") ? atoi(getenv("R2")) : 0, getenv("R4") ? atoi(getenv("R4")) : 0);
}
```

```cpp
#include <cuda_runtime.h>
#include <cuda_bf16.h>
#include <cuda.h>
#include <stdint.h>

namespace {

constexpr int NCTA = 132, NWARP = 8, NTHR = 256;
constexpr int DM = 512, SK = 65536, FF = 1792;
constexpr int WPH = NCTA;
constexpr int SLOT_BYTES = 8192;
constexpr int KEEP_H = 760;
constexpr int RESET_X = 400;
constexpr int STOP_X = 700;
constexpr int WO_K = 25;
constexpr int WO_R0 = 60;
constexpr int STOP_R = -80;
constexpr int NSTAT = 2;
constexpr int T_DYN = 6 * 132 + 66;
constexpr int T_LAST = 4096 - 132;
constexpr int N_ALL = T_LAST - T_DYN;
constexpr int N_DYN = N_ALL - KEEP_H;
constexpr int KCAP = 12;
static_assert(KCAP * 99 > KEEP_H, "the warps that stream to the end must be able to take all kept tiles");
static_assert(N_DYN - STOP_X >= NSTAT * 132, "");

constexpr int WARP_BYTES = 28672;
constexpr int O_W = 8192, O_C0 = 12288, O_C1 = 18432, O_E = 24576, O_P = 27648;
constexpr int SM_BAR = NWARP * WARP_BYTES;
constexpr int SM_STAT = SM_BAR + 320;
constexpr int SM_Q = SM_STAT + 128;
constexpr int Q_PITCH = 272;
constexpr int SM_LIST = SM_Q + 2 * 4 * Q_PITCH;
constexpr int SM_ML = SM_LIST + NWARP * KCAP * 2;
constexpr int SM_TOTAL = SM_ML + NWARP * 32;
static_assert(SM_TOTAL <= 232448, "");

struct Scratch {
  uint32_t QX[2][2048];
  uint32_t PO[2][8][17][256];
  uint32_t ML[2][8][17][8];
  uint32_t Y1[2][8][512];
  uint32_t GU[2][2 * FF];
  uint32_t Y2[2][7][512];
  uint32_t cnt[2][32];
  uint32_t ctr[2][8][32];
};
__device__ __align__(1024) Scratch g_s;

struct Maps { CUtensorMap k, v, wq, wo, wg, wu, wd; };

constexpr int SPIN_LIMIT = 1 << 22;

__device__ __forceinline__ void mbar_init(uint32_t bar, int cnt) {
  asm volatile("mbarrier.init.shared::cta.b64 [%0], %1;" ::"r"(bar), "r"(cnt) : "memory");
}
__device__ __forceinline__ void mbar_expect(uint32_t bar, uint32_t bytes) {
  asm volatile("mbarrier.arrive.expect_tx.shared::cta.b64 _, [%0], %1;" ::"r"(bar), "r"(bytes) : "memory");
}
__device__ __forceinline__ void mbar_wait(uint32_t bar, uint32_t parity) {
  uint32_t ok;
  int it = 0;
  do {
    asm volatile("{.reg .pred p; mbarrier.try_wait.parity.shared::cta.b64 p, [%1], %2; selp.u32 %0,1,0,p;}"
                 : "=r"(ok) : "r"(bar), "r"(parity) : "memory");
    if (++it > SPIN_LIMIT) __trap();
  } while (!__all_sync(0xffffffffu, ok));
}
__device__ __forceinline__ bool mbar_test(uint32_t bar, uint32_t parity) {
  uint32_t ok;
  asm volatile("{.reg .pred p; mbarrier.test_wait.parity.shared::cta.b64 p, [%1], %2; selp.u32 %0,1,0,p;}"
               : "=r"(ok) : "r"(bar), "r"(parity) : "memory");
  return ok != 0;
}
__device__ __forceinline__ int fresh_lane() { int l; asm volatile("mov.u32 %0, %laneid;" : "=r"(l)); return l; }
template <class T> __device__ __forceinline__ T* pin(T* p) { asm volatile("" : "+l"(p)); return p; }
__device__ __forceinline__ int opaque(int x) { asm volatile("" : "+r"(x)); return x; }
__device__ __forceinline__ void tma3d(uint32_t dst, const CUtensorMap* m, int row, uint32_t bar, uint64_t pol) {
  asm volatile("cp.async.bulk.tensor.3d.shared::cluster.global.mbarrier::complete_tx::bytes.L2::cache_hint"
               " [%0], [%1, {%3, %4, %3}], [%2], %5;"
               ::"r"(dst), "l"(m), "r"(bar), "r"(0), "r"(row), "l"(pol) : "memory");
}
__device__ __forceinline__ void tma2d(uint32_t dst, const CUtensorMap* m, int col, int row, uint32_t bar, uint64_t pol) {
  asm volatile("cp.async.bulk.tensor.2d.shared::cluster.global.mbarrier::complete_tx::bytes.L2::cache_hint"
               " [%0], [%1, {%3, %4}], [%2], %5;"
               ::"r"(dst), "l"(m), "r"(bar), "r"(col), "r"(row), "l"(pol) : "memory");
}
__device__ __forceinline__ void l2_prefetch(const void* p, uint32_t bytes) {
  asm volatile("cp.async.bulk.prefetch.L2.global [%0], %1;" ::"l"(p), "r"(bytes) : "memory");
}
__device__ __forceinline__ uint64_t pol_evict_first() {
  uint64_t p;
  asm volatile("createpolicy.fractional.L2::evict_first.b64 %0, 1.0;" : "=l"(p));
  return p;
}
__device__ __forceinline__ void ldsm4(uint32_t& a, uint32_t& b, uint32_t& c, uint32_t& d, uint32_t addr) {
  asm volatile("ldmatrix.sync.aligned.m8n8.x4.shared.b16 {%0,%1,%2,%3}, [%4];"
               : "=r"(a), "=r"(b), "=r"(c), "=r"(d) : "r"(addr) : "memory");
}
__device__ __forceinline__ void ldsm4t(uint32_t& a, uint32_t& b, uint32_t& c, uint32_t& d, uint32_t addr) {
  asm volatile("ldmatrix.sync.aligned.m8n8.x4.trans.shared.b16 {%0,%1,%2,%3}, [%4];"
               : "=r"(a), "=r"(b), "=r"(c), "=r"(d) : "r"(addr) : "memory");
}
__device__ __forceinline__ void mma(float (&c)[4], uint32_t a0, uint32_t a1, uint32_t a2, uint32_t a3,
                                    uint32_t b0, uint32_t b1) {
  asm volatile("mma.sync.aligned.m16n8k16.row.col.f32.bf16.bf16.f32 {%0,%1,%2,%3}, {%4,%5,%6,%7}, {%8,%9}, {%0,%1,%2,%3};"
               : "+f"(c[0]), "+f"(c[1]), "+f"(c[2]), "+f"(c[3])
               : "r"(a0), "r"(a1), "r"(a2), "r"(a3), "r"(b0), "r"(b1));
}
__device__ __forceinline__ uint32_t movm(uint32_t a) {
  uint32_t d;
  asm volatile("movmatrix.sync.aligned.m8n8.trans.b16 %0, %1;" : "=r"(d) : "r"(a));
  return d;
}
__device__ __forceinline__ uint32_t pack2(float lo, float hi) {
  uint32_t d;
  asm("cvt.rn.bf16x2.f32 %0, %1, %2;" : "=r"(d) : "f"(hi), "f"(lo));
  return d;
}
__device__ __forceinline__ float lo16(uint32_t w) { return __uint_as_float(w << 16); }
__device__ __forceinline__ float hi16(uint32_t w) { return __uint_as_float(w & 0xffff0000u); }
__device__ __forceinline__ float rbf(float x) { return lo16(pack2(x, 0.f)); }
__device__ __forceinline__ float ex2(float x) {
  float y;
  asm("ex2.approx.ftz.f32 %0, %1;" : "=f"(y) : "f"(x));
  return y;
}
__device__ __forceinline__ float rcp(float x) {
  float y;
  asm("rcp.approx.ftz.f32 %0, %1;" : "=f"(y) : "f"(x));
  return y;
}
__device__ __forceinline__ uint32_t enc(uint32_t w) { return w ? w : 0x80000000u; }
__device__ __forceinline__ uint32_t ldr32(const uint32_t* p) {
  uint32_t v;
  asm volatile("ld.relaxed.gpu.global.u32 %0, [%1];" : "=r"(v) : "l"(p) : "memory");
  return v;
}
__device__ __forceinline__ void ldr64(uint32_t& a, uint32_t& b, const uint32_t* p) {
  asm volatile("ld.relaxed.gpu.global.v2.u32 {%0,%1}, [%2];" : "=r"(a), "=r"(b) : "l"(p) : "memory");
}
__device__ __forceinline__ void str32(uint32_t* p, uint32_t v) {
  asm volatile("st.relaxed.gpu.global.u32 [%0], %1;" ::"l"(p), "r"(v) : "memory");
}
__device__ __forceinline__ void str64(uint32_t* p, uint32_t a, uint32_t b) {
  asm volatile("st.relaxed.gpu.global.v2.u32 [%0], {%1,%2};" ::"l"(p), "r"(a), "r"(b) : "memory");
}
__device__ __forceinline__ void sts32(uint32_t addr, uint32_t v) {
  asm volatile("st.shared.u32 [%0], %1;" ::"r"(addr), "r"(v) : "memory");
}
__device__ __forceinline__ void stsf(uint32_t addr, float v) {
  asm volatile("st.shared.f32 [%0], %1;" ::"r"(addr), "f"(v) : "memory");
}
__device__ __forceinline__ void stsf2(uint32_t addr, float a, float b) {
  asm volatile("st.shared.v2.f32 [%0], {%1,%2};" ::"r"(addr), "f"(a), "f"(b) : "memory");
}
__device__ __forceinline__ float ldsf(uint32_t addr) {
  float v;
  asm volatile("ld.shared.f32 %0, [%1];" : "=f"(v) : "r"(addr) : "memory");
  return v;
}
__device__ __forceinline__ void ldsf2(float& a, float& b, uint32_t addr) {
  asm volatile("ld.shared.v2.f32 {%0,%1}, [%2];" : "=f"(a), "=f"(b) : "r"(addr) : "memory");
}
__device__ __forceinline__ void fence_async() { asm volatile("fence.proxy.async.shared::cta;" ::: "memory"); }

constexpr float SCALE_C = 0.08838834764831845f * 1.4426950408889634f;

struct Attn {
  float o[4][4];
  float m0, m1, l0, l1;
};

__device__ __forceinline__ void softmax_step(Attn& st, const float (&s)[4], uint32_t& r0, uint32_t& r1) {
  float t0 = fmaxf(s[0], s[2]), t1 = fmaxf(s[1], s[3]);
#pragma unroll
  for (int o = 4; o <= 16; o <<= 1) {
    t0 = fmaxf(t0, __shfl_xor_sync(0xffffffffu, t0, o));
    t1 = fmaxf(t1, __shfl_xor_sync(0xffffffffu, t1, o));
  }
  float n0 = fmaxf(st.m0, t0 * SCALE_C), n1 = fmaxf(st.m1, t1 * SCALE_C);
  float a0 = ex2(st.m0 - n0), a1 = ex2(st.m1 - n1);
  st.m0 = n0; st.m1 = n1;
  float p0 = ex2(fmaf(s[0], SCALE_C, -n0)), p1 = ex2(fmaf(s[1], SCALE_C, -n1));
  float p2 = ex2(fmaf(s[2], SCALE_C, -n0)), p3 = ex2(fmaf(s[3], SCALE_C, -n1));
  r0 = movm(pack2(p0, p1));
  r1 = movm(pack2(p2, p3));
  st.l0 = fmaf(st.l0, a0, p0 + p2);
  st.l1 = fmaf(st.l1, a1, p1 + p3);
#pragma unroll
  for (int i = 0; i < 4; i++) {
    st.o[i][0] *= a0; st.o[i][1] *= a1; st.o[i][2] *= a0; st.o[i][3] *= a1;
  }
}

__device__ __forceinline__ void tile_smem(Attn& st, uint32_t kaddr, uint32_t vaddr, uint32_t qaddr, bool lowg) {
  float s[4] = {0.f, 0.f, 0.f, 0.f}, s2[4] = {0.f, 0.f, 0.f, 0.f};
#pragma unroll
  for (int j = 0; j < 4; j++) {
    uint32_t q0, q1, q2, q3, a0, a1, a2, a3, c0, c1, c2, c3;
    ldsm4(q0, q1, q2, q3, qaddr + j * 64);
    ldsm4(a0, a1, a2, a3, (kaddr ^ (((2 * j) & 3) << 5)) + (j >> 1) * 2048);
    ldsm4(c0, c1, c2, c3, (kaddr ^ (((2 * j + 1) & 3) << 5)) + (j >> 1) * 2048);
    mma(s, a0, a1, a2, a3, q0, q1);
    mma(s2, c0, c1, c2, c3, q2, q3);
  }
#pragma unroll
  for (int i = 0; i < 4; i++) s[i] += s2[i];
  uint32_t r0, r1;
  softmax_step(st, s, r0, r1);
#pragma unroll
  for (int kg = 0; kg < 2; kg++) {
    uint32_t r = kg ? r1 : r0;
    uint32_t b0 = lowg ? r : 0u, b1 = lowg ? 0u : r;
#pragma unroll
    for (int mt = 0; mt < 4; mt++) {
      uint32_t a0, a1, a2, a3;
      ldsm4t(a0, a1, a2, a3, (vaddr ^ (mt << 5)) + kg * 1024);
      mma(st.o[mt], a0, a1, a2, a3, b0, b1);
    }
  }
}

__device__ __forceinline__ void lds128(uint32_t& a, uint32_t& b, uint32_t& c, uint32_t& d, uint32_t addr) {
  asm volatile("ld.shared.v4.u32 {%0,%1,%2,%3}, [%4];" : "=r"(a), "=r"(b), "=r"(c), "=r"(d) : "r"(addr) : "memory");
}
__device__ __forceinline__ void sts128(uint32_t addr, uint32_t a, uint32_t b, uint32_t c, uint32_t d) {
  asm volatile("st.shared.v4.u32 [%0], {%1,%2,%3,%4};" ::"r"(addr), "r"(a), "r"(b), "r"(c), "r"(d) : "memory");
}

constexpr uint32_t PK_M = 0x78007800u, PK_S = 0x80008000u;
constexpr int EXC_CAP = 25;

__device__ __forceinline__ uint32_t lds32(uint32_t addr) {
  uint32_t v;
  asm volatile("ld.shared.u32 %0, [%1];" : "=r"(v) : "r"(addr) : "memory");
  return v;
}

__device__ __forceinline__ bool pack_prepare(uint32_t img, int lane, int r, uint32_t& bases, uint32_t& exc, uint32_t& cnt) {
  bool ok = true;
  bases = 0;
  uint32_t c = cnt;
#pragma unroll 1
  for (int h = 0; h < 2; h++) {
    const uint32_t base = img + h * 4096 + lane * 16;
    uint32_t mx = 0u, mn = 0xffffffffu;
#pragma unroll
    for (int i = 0; i < 8; i++) {
      uint32_t w0, w1, w2, w3;
      lds128(w0, w1, w2, w3, base + i * 512);
      w0 &= ~PK_S; w1 &= ~PK_S; w2 &= ~PK_S; w3 &= ~PK_S;
      mx = __vimax3_u16x2(mx, w0, w1); mx = __vimax3_u16x2(mx, w2, w3);
      mn = __viaddmin_u16x2(w0, 0xffffffffu, mn); mn = __viaddmin_u16x2(w1, 0xffffffffu, mn);
      mn = __viaddmin_u16x2(w2, 0xffffffffu, mn); mn = __viaddmin_u16x2(w3, 0xffffffffu, mn);
    }
    const uint32_t e = __reduce_max_sync(0xffffffffu, max(mx & 0xffffu, mx >> 16)) >> 7;
    const uint32_t B = e > 15u ? e - 15u : 0u, thr = B << 7;
    bases |= B << (8 * h);
    uint32_t todo = __ballot_sync(0xffffffffu, min(mn & 0xffffu, mn >> 16) < thr);
    if (__popc(todo) > 8) ok = false;
    while (todo && ok) {
      const int src = __ffs(todo) - 1;
      todo &= todo - 1;
      const uint32_t off = h * 4096 + src * 16 + (lane >> 2) * 512 + (lane & 3) * 4;
      const uint32_t w = lds32(img + off);
#pragma unroll 1
      for (int j = 0; j < 2; j++) {
        const uint32_t v = j ? w >> 16 : w & 0xffffu;
        uint32_t m = __ballot_sync(0xffffffffu, (v & 0x7fffu) - 1u < thr);
        if (c + __popc(m) > EXC_CAP) { ok = false; break; }
        while (m) {
          const uint32_t en = __shfl_sync(0xffffffffu, (v << 16) | (r << 12) | ((off >> 1) + j), __ffs(m) - 1);
          m &= m - 1;
          if (lane == (int)c) exc = en;
          c++;
        }
      }
    }
  }
  if (ok) cnt = c;
  return ok;
}

__device__ __forceinline__ void pack4(uint32_t& p0, uint32_t& p1, uint32_t& p2, uint32_t w0, uint32_t w1, uint32_t w2,
                                      uint32_t w3, uint32_t nb) {
  const uint32_t x0 = __viaddmax_s16x2(w0 & ~PK_S, nb, 0u), x1 = __viaddmax_s16x2(w1 & ~PK_S, nb, 0u);
  const uint32_t x2 = __viaddmax_s16x2(w2 & ~PK_S, nb, 0u), x3 = __viaddmax_s16x2(w3 & ~PK_S, nb, 0u);
  p0 = x0 | (w0 & PK_S) | ((x3 << 11) & PK_M);
  p1 = x1 | (w1 & PK_S) | ((x3 << 7) & PK_M);
  p2 = x2 | (w2 & PK_S) | ((x3 << 3) & 0x38003800u) | ((w3 >> 1) & 0x40004000u);
}
__device__ __forceinline__ void unpack4_store(uint32_t addr, uint32_t p0, uint32_t p1, uint32_t p2, uint32_t thr) {
  const uint32_t x3 = ((p0 >> 11) & 0x000f000fu) | ((p1 >> 7) & 0x00f000f0u) | ((p2 >> 3) & 0x07000700u);
  sts128(addr, (p0 & ~PK_M) + __vminu2(p0 & 0x07ff07ffu, 0x00010001u) * thr,
         (p1 & ~PK_M) + __vminu2(p1 & 0x07ff07ffu, 0x00010001u) * thr,
         (p2 & ~PK_M) + __vminu2(p2 & 0x07ff07ffu, 0x00010001u) * thr,
         (x3 | ((p2 << 1) & PK_S)) + __vminu2(x3, 0x00010001u) * thr);
}
__device__ __forceinline__ uint32_t neg_base(uint32_t b) { return ((0u - (b << 7)) & 0xffffu) * 0x00010001u; }

__device__ __forceinline__ void grab_tile(uint32_t (&p)[48], uint32_t src) {
#pragma unroll
  for (int i = 0; i < 48; i++) p[i] = lds32(src + i * 128);
}
__device__ __forceinline__ void drop_tile(const uint32_t (&p)[48], uint32_t dst) {
#pragma unroll
  for (int i = 0; i < 48; i++) sts32(dst + i * 128, p[i]);
}
__device__ __forceinline__ void pack_tile_smem(uint32_t pk, uint32_t pv, uint32_t img, int lane, uint32_t bases) {
#pragma unroll 1
  for (int h = 0; h < 4; h++) {
    const uint32_t nb = neg_base((bases >> (8 * (h >> 1))) & 0xffu);
    const uint32_t src = img + h * 2048 + lane * 16, dst = ((h & 2) ? pv : pk) + (h & 1) * 1536 + lane * 4;
    uint32_t p[12];
#pragma unroll
    for (int i = 0; i < 4; i++) {
      uint32_t w0, w1, w2, w3;
      lds128(w0, w1, w2, w3, src + i * 512);
      pack4(p[3 * i], p[3 * i + 1], p[3 * i + 2], w0, w1, w2, w3, nb);
    }
    __syncwarp();
#pragma unroll
    for (int i = 0; i < 12; i++) sts32(dst + i * 128, p[i]);
  }
}
__device__ __forceinline__ void unpack_tile_smem(uint32_t pk, uint32_t pv, uint32_t img, int lane, uint32_t bases) {
#pragma unroll 1
  for (int h = 0; h < 4; h++) {
    const uint32_t thr = ((bases >> (8 * (h >> 1))) & 0xffu) << 7;
    const uint32_t dst = img + h * 2048 + lane * 16, src = ((h & 2) ? pv : pk) + (h & 1) * 1536 + lane * 4;
    uint32_t p[12];
#pragma unroll
    for (int i = 0; i < 12; i++) p[i] = lds32(src + i * 128);
    __syncwarp();
#pragma unroll
    for (int i = 0; i < 4; i++) unpack4_store(dst + i * 512, p[3 * i], p[3 * i + 1], p[3 * i + 2], thr);
  }
}

template <int H>
__device__ __forceinline__ void w_frags(uint32_t (&A)[32], uint32_t seg, int lane) {
  const int row = (lane & 7) + ((lane >> 4) << 3);
  const uint32_t base = seg + row * 64 + ((((lane >> 3) & 1) ^ ((row >> 1) & 3)) << 4);
#pragma unroll
  for (int i = 0; i < 4; i++)
    ldsm4t(A[16 * H + 4 * i], A[16 * H + 4 * i + 1], A[16 * H + 4 * i + 2], A[16 * H + 4 * i + 3],
           (base ^ ((i & 1) << 5)) + (i >> 1) * 1024);
}

template <int NKS, bool LN, int FMT>
__device__ __forceinline__ void gemv_regs(const uint32_t (&A)[32], uint32_t sb, int warp, int lane, uint32_t xw,
                                          uint32_t* dst, bool real) {
  float acc[2][4] = {{0.f, 0.f, 0.f, 0.f}, {0.f, 0.f, 0.f, 0.f}};
  const int t = lane & 3, g = lane >> 2;
  float s1 = lo16(xw) + hi16(xw), s2 = fmaf(lo16(xw), lo16(xw), hi16(xw) * hi16(xw));
#pragma unroll
  for (int ks = 0; ks < NKS; ks++) {
    const uint32_t x0 = __shfl_sync(0xffffffffu, xw, 8 * ks + t);
    const uint32_t x1 = __shfl_sync(0xffffffffu, xw, 8 * ks + 4 + t);
    const uint32_t b0 = (LN && (g & 1)) ? 0x3f803f80u : x0, b1 = (LN && (g & 1)) ? 0x3f803f80u : x1;
    mma(acc[0], A[8 * ks], A[8 * ks + 1], A[8 * ks + 2], A[8 * ks + 3], b0, b1);
    mma(acc[1], A[8 * ks + 4], A[8 * ks + 5], A[8 * ks + 6], A[8 * ks + 7], b0, b1);
    if (LN) {
      s1 += __shfl_xor_sync(0xffffffffu, s1, 16 >> ks);
      s2 += __shfl_xor_sync(0xffffffffu, s2, 16 >> ks);
    }
  }
  if (LN) {
    s1 += __shfl_xor_sync(0xffffffffu, s1, 1);
    s2 += __shfl_xor_sync(0xffffffffu, s2, 1);
  }
  const float v = (t & 2) ? ((t & 1) ? acc[1][2] : acc[1][0]) : ((t & 1) ? acc[0][2] : acc[0][0]);
  if (LN) {
    const float cs = (t & 2) ? ((t & 1) ? acc[1][3] : acc[1][1]) : ((t & 1) ? acc[0][3] : acc[0][1]);
    stsf2(sb + SM_Q + (warp * 32 + 8 * t + g) * 8, v, cs);
    if (lane == 0) stsf2(sb + SM_STAT + warp * 8, s2, s1);
  } else {
    stsf(sb + SM_Q + (warp * 32 + 8 * t + g) * 4, v);
  }
  dst = pin(dst);
  uint32_t ra = sb + SM_Q + lane * (LN ? 8 : 4);
  asm volatile("" : "+r"(ra));
  __syncthreads();
  if (warp == 0) {
    float y;
    if (LN) {
      float u[8], c[8], q[8], m[8];
#pragma unroll
      for (int w = 0; w < 8; w++) ldsf2(q[w], m[w], sb + SM_STAT + w * 8);
#pragma unroll
      for (int w = 0; w < 8; w++) ldsf2(u[w], c[w], ra + w * 256);
      const float mean = (((m[0] + m[1]) + (m[2] + m[3])) + ((m[4] + m[5]) + (m[6] + m[7]))) * (1.f / 512.f);
      const float msq = (((q[0] + q[1]) + (q[2] + q[3])) + ((q[4] + q[5]) + (q[6] + q[7]))) * (1.f / 512.f);
      const float vb = rbf(fmaxf(fmaf(-mean, mean, msq), 0.f));
      float sq, rs;
      asm("sqrt.approx.ftz.f32 %0, %1;" : "=f"(sq) : "f"(rbf(vb + 1e-5f)));
      asm("rcp.approx.ftz.f32 %0, %1;" : "=f"(rs) : "f"(rbf(sq)));
      y = ((u[0] + u[1]) + (u[2] + u[3])) + ((u[4] + u[5]) + (u[6] + u[7]));
      const float cs = ((c[0] + c[1]) + (c[2] + c[3])) + ((c[4] + c[5]) + (c[6] + c[7]));
      y = fmaf(-rbf(mean), cs, y) * rs;
    } else {
      float u[8];
#pragma unroll
      for (int w = 0; w < 8; w++) u[w] = ldsf(ra + w * 128);
      y = ((u[0] + u[1]) + (u[2] + u[3])) + ((u[4] + u[5]) + (u[6] + u[7]));
    }
    uint32_t o;
    if (FMT == 2) o = pack2(y, __shfl_down_sync(0xffffffffu, y, 1));
    else o = __float_as_uint(FMT == 1 ? rbf(y) : y);
    o = enc(o);
    asm volatile("{.reg .pred p; setp.ne.u32 p, %2, 0; @p st.relaxed.gpu.global.u32 [%0], %1;}"
                 ::"l"(dst), "r"(o), "r"((uint32_t)(real && (FMT != 2 || !(lane & 1)))) : "memory");
  }
}

template <int NP, class F, class G>
__device__ __forceinline__ uint32_t add_partials(const uint32_t* p, uint32_t xw, bool real, F side, G after) {
  uint32_t a[NP], b[NP];
#pragma unroll
  for (int k = 0; k < NP; k++) a[k] = b[k] = 0u;
  int it = 0;
  bool pend, done = false;
  if (real) do {
#pragma unroll
    for (int k = 0; k < NP; k++)
      if (a[k] == 0u || b[k] == 0u) ldr64(a[k], b[k], p + k * 512);
    if (!done) done = side();
    const uint32_t m0 = __vimin3_u32(__vimin3_u32(a[0], b[0], a[1]), __vimin3_u32(b[1], a[2], b[2]), __vimin3_u32(a[3], b[3], a[4]));
    const uint32_t m1 = __vimin3_u32(__vimin3_u32(b[4], a[5], b[5]), __vimin3_u32(a[6], b[6], a[NP - 1]), b[NP - 1]);
    pend = min(m0, m1) == 0u;
    if (!done) done = side();
    if (++it > SPIN_LIMIT) __trap();
  } while (__any_sync(0xffffffffu, pend) || !done);
  auto f = [](uint32_t u) { return __uint_as_float(u); };
  float y0 = ((f(a[0]) + f(a[1])) + (f(a[2]) + f(a[3]))) + ((f(a[4]) + f(a[5])) + (NP == 8 ? f(a[6]) + f(a[NP - 1]) : f(a[6])));
  float y1 = ((f(b[0]) + f(b[1])) + (f(b[2]) + f(b[3]))) + ((f(b[4]) + f(b[5])) + (NP == 8 ? f(b[6]) + f(b[NP - 1]) : f(b[6])));
  asm volatile("" : "+f"(y0), "+f"(y1));
  after();
  return pack2(lo16(xw) + rbf(y0), hi16(xw) + rbf(y1));
}

__global__ void __launch_bounds__(NTHR, 1)
decode_kernel(const __grid_constant__ Maps maps, const uint32_t* __restrict__ x_in,
              const char* __restrict__ Kp, const char* __restrict__ Vp, uint32_t* __restrict__ out) {
  extern __shared__ __align__(1024) unsigned char smem[];
  const uint32_t sb = (uint32_t)__cvta_generic_to_shared(smem);
  const int tid = threadIdx.x, lane = tid & 31;
  const int warp = __shfl_sync(0xffffffffu, tid >> 5, 0);
  const int cta = blockIdx.x;
  const int head_lo = cta < 128 ? ((cta + 3 * (cta >> 3)) & 7) : 2 * (cta - 128), head_hi = cta < 128 ? head_lo : head_lo + 1;
  const int head = warp < 4 ? head_lo : head_hi;
  const int jw = cta < 128 ? (cta >> 3) * 8 + warp : 128 + (warp & 3);
  const uint32_t ring = sb + warp * WARP_BYTES;
  const uint32_t rbar = sb + SM_BAR + warp * 40;
  const uint32_t wbar = rbar + 24;
  const uint32_t wseg = ring + O_W;

  auto w_issue = [&](int half, const CUtensorMap* m, int col, int row) {
    if (lane == 0) {
      mbar_expect(wbar + half * 8, 2048);
      tma2d(wseg + half * 2048, m, col, row, wbar + half * 8, pol_evict_first());
    }
    __syncwarp();
  };
  auto issue_demote = [&](int sl, int t) {
    if (lane == 0) {
      uint64_t pn;
      asm volatile("createpolicy.fractional.L2::evict_normal.b64 %0, 1.0;" : "=l"(pn));
      const uint64_t pf = pol_evict_first();
      const int row = head * SK + t * 16;
      const uint32_t dst = ring + sl * SLOT_BYTES, b = rbar + sl * 8;
      mbar_expect(b, SLOT_BYTES);
      tma3d(dst, &maps.k, row, b, pn);
      asm volatile("cp.async.bulk.prefetch.L2.global.L2::cache_hint [%0], %1, %2;" ::"l"(Kp + (size_t)row * 256), "r"(4096), "l"(pf) : "memory");
      tma3d(dst + 4096, &maps.v, row, b, pn);
      asm volatile("cp.async.bulk.prefetch.L2.global.L2::cache_hint [%0], %1, %2;" ::"l"(Vp + (size_t)row * 256), "r"(4096), "l"(pf) : "memory");
    }
    __syncwarp();
  };
  auto issue = [&](int sl, int t, bool kp) {
    if (lane == 0) {
      const uint64_t pf = pol_evict_first();
      const int row = head * SK + t * 16;
      const uint32_t dst = ring + sl * SLOT_BYTES, b = rbar + sl * 8;
      mbar_expect(b, SLOT_BYTES);
      tma3d(dst, &maps.k, row, b, pf);
      if (kp) l2_prefetch(Kp + (size_t)row * 256, 4096);
      tma3d(dst + 4096, &maps.v, row, b, pf);
      if (kp) l2_prefetch(Vp + (size_t)row * 256, 4096);
    }
    __syncwarp();
  };
  auto stack_tile = [&](uint32_t r) -> int { return r == 5 ? 6 * WPH + (jw >> 1) : jw + (r == 6 ? 5 : (int)r) * WPH; };

  uint32_t xw = __ldg(x_in + tid);
  if (lane == 0) {
    if (sb & 1023) __trap();
#pragma unroll
    for (int i = 0; i < 5; i++) mbar_init(rbar + i * 8, 1);
    asm volatile("fence.mbarrier_init.release.cluster;" ::: "memory");
    fence_async();
  }
  if (cta < 128) { w_issue(0, &maps.wq, cta * 32, warp * 64); w_issue(1, &maps.wq, cta * 32, warp * 64 + 32); }
  if (tid == 0 && cta < 128 && (cta & 15) == 0) {
    g_s.ctr[0][cta >> 4][0] = 0;
    asm volatile("fence.acq_rel.gpu;" ::: "memory");
  }
  __syncwarp();
  issue_demote(2, jw);
  if (tid == 32) {
    asm volatile("prefetch.tensormap [%0];" ::"l"(&maps.wo) : "memory");
    asm volatile("prefetch.tensormap [%0];" ::"l"(&maps.wg) : "memory");
    asm volatile("prefetch.tensormap [%0];" ::"l"(&maps.wu) : "memory");
    asm volatile("prefetch.tensormap [%0];" ::"l"(&maps.wd) : "memory");
  }
  __syncwarp();

  uint32_t c0[48], c1[48], c2[48], c3[48];
#pragma unroll
  for (int i = 0; i < 48; i++) { c0[i] = 0; c1[i] = 0; c2[i] = 0; c3[i] = 0; }
  uint32_t exc = 0;

  uint32_t sst = 0;

  for (int layer = -1; layer < 2; layer++) {
    const bool live = layer >= 0;
    const int ly = live ? layer : 0;

    if (live) {
      Attn st;
#pragma unroll
      for (int i = 0; i < 4; i++) { st.o[i][0] = st.o[i][1] = st.o[i][2] = st.o[i][3] = 0.f; }
      st.m0 = st.m1 = -INFINITY; st.l0 = st.l1 = 0.f;
      const int ln = fresh_lane();
      const uint32_t koff = ((ln & 7) + ((ln >> 3) & 1) * 8) * 128 + (((ln >> 4) ^ (ln & 7)) << 4);
      const uint32_t voff = 4096 + (ln >> 4) * 2048 + (ln & 7) * 128 + ((((ln >> 3) & 1) ^ (ln & 7)) << 4);
      const uint32_t qaddr = sb + SM_Q + ((head - head_lo) * 4 + (ln & 3)) * Q_PITCH + (ln >> 3) * 16;
      const bool lowg = ln < 16;
      int nxt = jw - NSTAT * WPH;
      if (layer == 0) { sst = 7; nxt += WPH; }
      else sst = ((sst ^ 0x10) & 0x3ff0770) | 1;
      while (true) {
        int sl = -1;
        if ((sst & 2) && mbar_test(rbar + 8, (sst >> 5) & 1)) sl = 1;
        if (sst & 4) sl = 2;
        if ((sst & 1) && mbar_test(rbar, (sst >> 4) & 1)) sl = 0;
        sl = __shfl_sync(0xffffffffu, sl, 0);
        if (sl >= 0) {
          tile_smem(st, ring + sl * SLOT_BYTES + koff, ring + sl * SLOT_BYTES + voff, qaddr, lowg);
          __syncwarp();
          sst ^= 0x11u << sl;
          if (sl == 0) sst |= 0x2000;
          if (layer == 0) {
            if (sl != 0 || (sst & 0x8000)) {
              const int l_ = fresh_lane();
              const uint32_t r = (sst >> 8) & 7, img = ring + sl * SLOT_BYTES;
              uint32_t bases, cnt = (sst >> 21) & 31;
              if (!pack_prepare(img, l_, r, bases, exc, cnt)) bases |= 0x10000;
              sst = ((sst & ~(31u << 21) & ~0x8000u) | (cnt << 21)) + ((r == 4 && (warp & 1)) ? 0x200 : 0x100);
              if (l_ == EXC_CAP + (int)r) exc = bases;
              const uint32_t pk = r < 4 ? img : ring + (r == 4 ? O_C1 : r == 5 ? O_E : O_C0);
              pack_tile_smem(pk, pk + (r == 5 ? WARP_BYTES : 3072), img, l_, bases);
              if (r == 0) grab_tile(c0, img + l_ * 4);
              else if (r == 1) grab_tile(c1, img + l_ * 4);
              else if (r == 2) grab_tile(c2, img + l_ * 4);
              else if (r == 3) grab_tile(c3, img + l_ * 4);
              fence_async();
              __syncwarp();
              if (sl == 1 && (sst & 0x700) < 0x600) { issue(1, stack_tile((sst >> 8) & 7), false); sst |= 2; }
            }
          } else if (sl == 1 && ((sst >> 16) & 31)) {
            sst -= 1u << 16;
            uint32_t t;
            asm volatile("ld.shared.u16 %0, [%1];" : "=r"(t) : "r"(sb + SM_LIST + warp * (KCAP * 2) + ((sst >> 16) & 31) * 2) : "memory");
            issue(1, t, false); sst |= 2;
          }
        } else if (layer == 1 && (sst & 0x700) && !(sst & 2) && ((sst & 0x2000) || !(sst & 1))) {
          const int l_ = fresh_lane();
          const uint32_t r = ((sst >> 8) & 7) - 1, img = ring + SLOT_BYTES;
          sst = ((sst - ((r == 6 && (warp & 1)) ? 0x200 : 0x100)) | 2) & ~0x2000u;
          const uint32_t hdr = __shfl_sync(0xffffffffu, exc, EXC_CAP + r);
          if (hdr & 0x10000) {
            issue(1, stack_tile(r), false);
          } else {
            const uint32_t pk = ring + (r <= 4 ? O_C1 : r == 5 ? O_E : O_C0);
            if (r == 0) drop_tile(c0, pk + l_ * 4);
            else if (r == 1) drop_tile(c1, pk + l_ * 4);
            else if (r == 2) drop_tile(c2, pk + l_ * 4);
            else if (r == 3) drop_tile(c3, pk + l_ * 4);
            unpack_tile_smem(pk, pk + (r == 5 ? WARP_BYTES : 3072), img, l_, hdr);
            __syncwarp();
            if (l_ < (int)((sst >> 21) & 31) && ((exc >> 12) & 7) == r)
              asm volatile("st.shared.u16 [%0], %1;" ::"r"(img + (exc & 0xfffu) * 2), "r"(exc >> 16) : "memory");
            fence_async();
            __syncwarp();
            if (l_ == 0) mbar_expect(rbar + 8, 0);
          }
          __syncwarp();
        } else if (warp == 7 && (sst & 0x88) == 8) {
          sst = (sst | 0x80) & ~0x2000u;
          const int l_ = fresh_lane(), c_ = opaque(cta), y_ = opaque(ly);
          const uint4 z = make_uint4(0, 0, 0, 0);
          const int s_lo = c_ >> 3;
          uint4* po = reinterpret_cast<uint4*>(&g_s.PO[y_][head_lo][s_lo][0]);
          po[l_] = z; po[l_ + 32] = z;
          if (l_ < 2) reinterpret_cast<uint4*>(&g_s.ML[y_][head_lo][s_lo][0])[l_] = z;
          if (head_hi != head_lo) {
            po = reinterpret_cast<uint4*>(&g_s.PO[y_][head_hi][16][0]);
            po[l_] = z; po[l_ + 32] = z;
            if (l_ < 2) reinterpret_cast<uint4*>(&g_s.ML[y_][head_hi][16][0])[l_] = z;
          }
          if (c_ < 128) {
            (&g_s.Y1[y_][0][0])[c_ * 32 + l_] = 0;
            if (y_ == 0 && l_ < 16) g_s.QX[1][c_ * 16 + l_] = 0;
          }
          if (c_ < 112) { g_s.GU[y_][c_ * 32 + l_] = 0; (&g_s.Y2[y_][0][0])[c_ * 32 + l_] = 0; }
          if (c_ < 8 && y_ == 0 && l_ == 0) g_s.ctr[1][c_][0] = 0;
          __syncwarp();
          if (l_ == 0) {
            asm volatile("fence.acq_rel.gpu;" ::: "memory");
            const uint32_t old = atomicAdd(&g_s.cnt[y_][0], 1u);
            sts32(sb + SM_STAT + 64, (old / NCTA + 1) * NCTA);
          }
          __syncwarp();
        } else if ((sst & 7) == 0) {
          break;
        } else if ((sst & 0x3080) == 0x2080) {
          uint32_t target, c;
          asm volatile("ld.shared.u32 %0, [%1];" : "=r"(target) : "r"(sb + SM_STAT + 64) : "memory");
          asm volatile("ld.acquire.gpu.global.u32 %0, [%1];" : "=r"(c) : "l"(&g_s.cnt[opaque(ly)][0]) : "memory");
          sst &= ~0x2000u;
          if (__all_sync(0xffffffffu, (int)(c - target) >= 0)) sst |= 0x1000;
        } else {
          int it = 0;
          while (!__any_sync(0xffffffffu, ((sst & 1) && mbar_test(rbar, (sst >> 4) & 1)) || ((sst & 2) && mbar_test(rbar + 8, (sst >> 5) & 1))))
            if (++it > (SPIN_LIMIT << 3)) __trap();
        }
        if (!(sst & 0x801) && !(layer == 1 && (warp & 3) == 0 && (sst & 0x700))) {
          if (layer == 0 && (sst & 0x700) == 0x600) {
            issue(0, stack_tile(6), false); sst |= 0x8001;
          } else {
            const int d = __shfl_sync(0xffffffffu, nxt, 8) + NSTAT * WPH;
            const int nd = layer == 0 ? N_ALL : N_DYN;
            if (d >= nd - RESET_X) sst |= 8;
            if (d < nd) {
              const bool kp = d >= N_DYN;
              issue(0, T_DYN + d, kp); sst |= 1;
              if (kp) {
                if (lane == 0)
                  asm volatile("st.shared.u16 [%0], %1;" ::"r"(sb + SM_LIST + warp * (KCAP * 2) + ((sst >> 16) & 31) * 2), "r"(T_DYN + d) : "memory");
                sst += 1u << 16;
              }
              const bool full = (layer == 0 && ((sst >> 16) & 31) == KCAP) || ((warp & 3) == 0 && d >= nd - STOP_X), stat = d < (NSTAT - 1) * WPH;
              nxt = full ? 1 << 20 : d - (NSTAT - 1) * WPH;
              if (layer == 0 && !stat && d < NSTAT * WPH) {
                asm volatile("{.reg .u32 t; ld.acquire.gpu.global.u32 t, [%0];}" ::"l"(&g_s.QX[0][head * 256]) : "memory");
              }
              asm volatile("{.reg .pred p; setp.ne.u32 p, %2, 0; @p atom.global.relaxed.gpu.inc.u32 %0, [%1], 0x7fffffff;}"
                           : "+r"(nxt) : "l"(&g_s.ctr[layer][head][0]), "r"((uint32_t)(lane == 8 && !full && !stat)) : "memory");
              __syncwarp();
            } else if (layer == 1) {
              sst |= 0x800;
            } else if ((sst & 0x700) == 0x700) {
              issue(0, T_LAST + jw, false); sst |= 0x801;
            }
          }
        }
      }
      int rank = __shfl_sync(0xffffffffu, nxt, 8) + NSTAT * WPH - (layer == 0 ? N_ALL : N_DYN);

      {
#pragma unroll
        for (int o = 4; o <= 16; o <<= 1) {
          st.l0 += __shfl_xor_sync(0xffffffffu, st.l0, o);
          st.l1 += __shfl_xor_sync(0xffffffffu, st.l1, o);
        }
        const int g = lane >> 2, t = lane & 3;
        const uint32_t a = ring + O_P + ((t & 1) * 128 + (t >> 1) * 64) * 4;
#pragma unroll
        for (int mt = 0; mt < 4; mt++) {
          sts32(a + ((16 * mt + g) ^ (8 * t)) * 4, pack2(st.o[mt][0], st.o[mt][1]));
          sts32(a + ((16 * mt + 8 + g) ^ (8 * t)) * 4, pack2(st.o[mt][2], st.o[mt][3]));
        }
        if (lane < 2)
          sts128(sb + SM_ML + warp * 32 + lane * 16, __float_as_uint(st.m0), __float_as_uint(st.l0),
                 __float_as_uint(st.m1), __float_as_uint(st.l1));
      }
      {
        const int hp = tid >> 7, d = tid & 127, odd = tid & 1, hq = 2 * hp + odd;
        uint32_t* ppo = pin(&g_s.PO[ly][head_lo][cta >> 3][hq * 64 + (d >> 1)]);
        uint32_t* pml = pin(&g_s.ML[ly][head_lo][cta >> 3][2 * hq]);
        uint32_t am = sb + SM_ML + hp * 16 + odd * 8;
        uint32_t ap = sb + O_P + (hp * 128 + ((d & ~1) ^ (8 * (hp + 2 * (d >> 6))))) * 4;
        uint32_t sel = odd ? 0x7632 : 0x5410;
        asm volatile("" : "+r"(am), "+r"(ap), "+r"(sel));
        if (cta < 128) {
          if (rank > 100000) rank = STOP_R;
          if (rank < WO_R0) {
            const uint32_t c0_ = clock();
            while (__any_sync(0xffffffffu, (uint32_t)clock() - c0_ < (uint32_t)((WO_R0 - rank) * WO_K))) {}
          }
          w_issue(0, &maps.wo, (cta & 15) * 32, (cta >> 4) * 512 + warp * 64);
        }
        __syncthreads();
        float mw[8], lw[8];
        uint32_t u[8];
#pragma unroll
        for (int w = 0; w < 8; w++) ldsf2(mw[w], lw[w], am + w * 32);
#pragma unroll
        for (int w = 0; w < 8; w++) {
          uint32_t x0, x1;
          asm volatile("ld.shared.v2.u32 {%0,%1}, [%2];" : "=r"(x0), "=r"(x1) : "r"(ap + w * WARP_BYTES) : "memory");
          u[w] = __byte_perm(x0, x1, sel);
        }
        const bool split = head_hi != head_lo;
        float Ma = fmaxf(fmaxf(mw[0], mw[1]), fmaxf(mw[2], mw[3]));
        float Mb = fmaxf(fmaxf(mw[4], mw[5]), fmaxf(mw[6], mw[7]));
        if (!split) Ma = Mb = fmaxf(Ma, Mb);
        float La = 0.f, a0 = 0.f, a1 = 0.f, Lb = 0.f, b0 = 0.f, b1 = 0.f;
#pragma unroll
        for (int w = 0; w < 4; w++) {
          const float ea = ex2(mw[w] - Ma), eb = ex2(mw[w + 4] - Mb);
          La = fmaf(lw[w], ea, La); a0 = fmaf(lo16(u[w]), ea, a0); a1 = fmaf(hi16(u[w]), ea, a1);
          Lb = fmaf(lw[w + 4], eb, Lb); b0 = fmaf(lo16(u[w + 4]), eb, b0); b1 = fmaf(hi16(u[w + 4]), eb, b1);
        }
        if (!split) { La += Lb; a0 += b0; a1 += b1; }
        if (d < 2) str64(pml, enc(__float_as_uint(Ma)), enc(__float_as_uint(La)));
        const float ia = rcp(La);
        str32(ppo, enc(pack2(a0 * ia, a1 * ia)));
        if (split) {
          if (d < 2) str64(pml + 17 * 8, enc(__float_as_uint(Mb)), enc(__float_as_uint(Lb)));
          const float ib = rcp(Lb);
          str32(ppo + 17 * 256, enc(pack2(b0 * ib, b1 * ib)));
        }
      }
      if (cta < 128) w_issue(1, &maps.wo, (cta & 15) * 32, (cta >> 4) * 512 + warp * 64 + 32);
      if (tid == 255 && !(sst & 0x1000)) {
        uint32_t target, c;
        asm volatile("ld.shared.u32 %0, [%1];" : "=r"(target) : "r"(sb + SM_STAT + 64) : "memory");
        int it = 0;
        do {
          asm volatile("ld.acquire.gpu.global.u32 %0, [%1];" : "=r"(c) : "l"(&g_s.cnt[ly][0]) : "memory");
          if (++it > SPIN_LIMIT) __trap();
        } while ((int)(c - target) < 0);
      }
      __syncwarp();
      __syncthreads();
    }

    if (cta < 128) {
      uint32_t A[32];
      if (live) {
#pragma unroll 1
        for (int real = 0; real < 2; real++) {
#pragma unroll
          for (int i = 0; i < 16; i++) A[i] = 0u;
          const int rb = cta >> 4;
          const uint32_t* pp = pin(&g_s.PO[ly][rb][0][tid]);
          const uint32_t* pm = pin(&g_s.ML[ly][rb][lane < 17 ? lane : 0][2 * (warp >> 1)]);
          uint32_t v[17], um = 0u, ul = 0u;
#pragma unroll
          for (int s = 0; s < 17; s++) v[s] = 0u;
          int it = 0;
          bool pend, done = false;
          if (real) {
            do {
              if (um == 0u || ul == 0u) ldr64(um, ul, pm);
#pragma unroll
              for (int s = 0; s < 17; s++)
                if (v[s] == 0u) v[s] = ldr32(pp + s * 256);
              if (!done && __all_sync(0xffffffffu, mbar_test(wbar, 1))) {
                w_frags<0>(A, wseg, lane);
                __syncwarp();
                if (cta < 112) w_issue(0, cta < 56 ? &maps.wg : &maps.wu, (cta < 56 ? cta : cta - 56) * 32, warp * 64);
                else if (layer == 0) w_issue(0, &maps.wq, cta * 32, warp * 64);
                done = true;
              }
              pend = __vimin3_u32(__vimin3_u32(__vimin3_u32(um, ul, v[0]), __vimin3_u32(v[1], v[2], v[3]), __vimin3_u32(v[4], v[5], v[6])),
                                  __vimin3_u32(__vimin3_u32(v[7], v[8], v[9]), __vimin3_u32(v[10], v[11], v[12]), __vimin3_u32(v[13], v[14], v[15])), v[16]) == 0u;
              if (++it > SPIN_LIMIT) __trap();
            } while (__any_sync(0xffffffffu, pend) || !done);
          }
          const float ms = __uint_as_float(um);
          int mi = __float_as_int(ms);
          mi = __reduce_max_sync(0xffffffffu, mi ^ ((mi >> 31) & 0x7fffffff));
          const float M = __int_as_float(mi ^ ((mi >> 31) & 0x7fffffff));
          const float e = lane < 17 ? __uint_as_float(ul) * ex2(ms - M) : 0.f;
          float L = 0.f, o0 = 0.f, o1 = 0.f, Lb = 0.f, p0 = 0.f, p1 = 0.f;
#pragma unroll
          for (int s = 0; s < 17; s++) {
            const float es = __shfl_sync(0xffffffffu, e, s);
            if (s & 1) { Lb += es; p0 = fmaf(es, lo16(v[s]), p0); p1 = fmaf(es, hi16(v[s]), p1); }
            else { L += es; o0 = fmaf(es, lo16(v[s]), o0); o1 = fmaf(es, hi16(v[s]), o1); }
          }
          o0 += p0; o1 += p1;
          asm volatile("" : "+f"(o0), "+f"(o1));
          if (real) mbar_wait(wbar + 8, cta < 112 ? layer ^ 1 : 1);
          w_frags<1>(A, wseg + 2048, lane);
          const float inv = rcp(L + Lb);
          gemv_regs<4, false, 0>(A, sb, warp, lane, pack2(o0 * inv, o1 * inv), &g_s.Y1[ly][0][0] + cta * 32 + lane, real);
          if (real) {
            if (cta < 112) w_issue(1, cta < 56 ? &maps.wg : &maps.wu, (cta < 56 ? cta : cta - 56) * 32, warp * 64 + 32);
            else if (layer == 0) w_issue(1, &maps.wq, cta * 32, warp * 64 + 32);
          }
          __syncthreads();
        }
#pragma unroll 1
        for (int real = 0; real < 2; real++) {
#pragma unroll
          for (int i = 0; i < 16; i++) A[i] = 0u;
          const uint32_t xn = add_partials<8>(pin(&g_s.Y1[ly][0][2 * tid]), xw, real, [&]() {
            if (cta >= 112) return true;
            if (!__all_sync(0xffffffffu, mbar_test(wbar, 0))) return false;
            w_frags<0>(A, wseg, lane);
            __syncwarp();
            w_issue(0, &maps.wd, (cta & 15) * 32, (cta >> 4) * 256 + warp * 32);
            return true;
          }, [&]() { if (real && cta < 112) mbar_wait(wbar + 8, layer); w_frags<1>(A, wseg + 2048, lane); });
          if (real) { xw = xn; }
          if (cta < 112) {
            gemv_regs<4, true, 1>(A, sb, warp, lane, xn, &g_s.GU[ly][cta * 32 + lane], real);
            if (real) {
              if (layer == 0) {
                w_issue(1, &maps.wq, cta * 32, warp * 64 + 32);
              }
            }
            __syncthreads();
          }
        }
        if (cta < 112) {
#pragma unroll 1
          for (int real = 0; real < 2; real++) {
#pragma unroll
            for (int i = 0; i < 16; i++) A[i] = 0u;
            const uint32_t* pg = pin(&g_s.GU[ly][(lane >> 4) * FF + (cta >> 4) * 256 + warp * 32 + (lane & 15) * 2]);
            uint32_t a = 0u, b = 0u;
            int it = 0;
            bool done = false;
            if (real) {
              do {
                if (a == 0u || b == 0u) ldr64(a, b, pg);
                if (!done && __all_sync(0xffffffffu, mbar_test(wbar, 1))) {
                  w_frags<0>(A, wseg, lane);
                  __syncwarp();
                  if (layer == 0) { w_issue(0, &maps.wq, cta * 32, warp * 64); }
                  done = true;
                }
                if (++it > SPIN_LIMIT) __trap();
              } while (__any_sync(0xffffffffu, a == 0u || b == 0u) || !done);
            }
            const float a0 = __uint_as_float(a), a1 = __uint_as_float(b);
            const float c0_ = __shfl_xor_sync(0xffffffffu, a0, 16), c1_ = __shfl_xor_sync(0xffffffffu, a1, 16);
            const float g0 = lane < 16 ? a0 : c0_, g1 = lane < 16 ? a1 : c1_;
            const float u0 = lane < 16 ? c0_ : a0, u1 = lane < 16 ? c1_ : a1;
            const uint32_t hw = pack2((g0 > 0.f ? g0 : g0 * 0.f) * u0, (g1 > 0.f ? g1 : g1 * 0.f) * u1);
            gemv_regs<2, false, 0>(A, sb, warp, lane, hw, &g_s.Y2[ly][0][0] + cta * 32 + lane, real);
            __syncthreads();
          }
        }
        if (layer == 1 && cta != 127) break;
        if (layer == 0 && warp == 4) {
          if (lane < 16) g_s.QX[0][cta * 16 + lane] = 0;
          __syncwarp();
        }
      }
#pragma unroll 1
      for (int real = live ? 0 : 1; real < 2; real++) {
#pragma unroll
        for (int i = 0; i < 16; i++) A[i] = 0u;
        if (!live) {
          mbar_wait(wbar, 0); mbar_wait(wbar + 8, 0);
          w_frags<0>(A, wseg, lane);
        }
        const uint32_t xn = add_partials<7>(pin(&g_s.Y2[ly][0][2 * tid]), xw, real && live, [&]() {
          if (layer == 1) return true;
          if (!__all_sync(0xffffffffu, mbar_test(wbar, 0) && mbar_test(wbar + 8, cta < 112 ? 1 : 0))) return false;
          w_frags<0>(A, wseg, lane);
          return true;
        }, [&]() { w_frags<1>(A, wseg + 2048, lane); });
        if (real && live) {
          xw = xn;
          if (layer == 1) { out[tid] = xn; return; }
        }
        gemv_regs<4, true, 2>(A, sb, warp, lane, xw, &g_s.QX[(layer + 1) & 1][cta * 16 + (lane >> 1)], real);
        if (!real) __syncthreads();
      }
    } else if (layer == 1) {
      break;
    }
    if (!live) {
      mbar_wait(rbar + 16, 0);
      issue_demote(1, jw + WPH);
    }
    __syncthreads();
    {
      const uint32_t* pq = &g_s.QX[layer + 1][head_lo * 256 + tid];
      uint32_t qv0 = 0u, qv1 = head_hi != head_lo ? 0u : 1u;
      int it = 0;
      do {
        if (qv0 == 0u) qv0 = ldr32(pq);
        if (qv1 == 0u) qv1 = ldr32(pq + 256);
        if (++it > SPIN_LIMIT) __trap();
      } while (__any_sync(0xffffffffu, qv0 == 0u || qv1 == 0u));
      if (!live) issue_demote(0, T_DYN + jw);
      sts32(sb + SM_Q + (tid >> 6) * Q_PITCH + (tid & 63) * 4, qv0);
      sts32(sb + SM_Q + (4 + (tid >> 6)) * Q_PITCH + (tid & 63) * 4, qv1);
    }
    __syncthreads();
  }
}

typedef CUresult (*EncodeFn)(CUtensorMap*, CUtensorMapDataType, cuuint32_t, void*, const cuuint64_t*,
                             const cuuint64_t*, const cuuint32_t*, const cuuint32_t*, CUtensorMapInterleave,
                             CUtensorMapSwizzle, CUtensorMapL2promotion, CUtensorMapFloatOOBfill);

void make_kv_map(EncodeFn enc, CUtensorMap* m, void* p) {
  cuuint64_t dims[3] = {64, (cuuint64_t)8 * SK, 2};
  cuuint64_t strides[2] = {256, 128};
  cuuint32_t box[3] = {64, 16, 2}, es[3] = {1, 1, 1};
  enc(m, CU_TENSOR_MAP_DATA_TYPE_BFLOAT16, 3, p, dims, strides, box, es, CU_TENSOR_MAP_INTERLEAVE_NONE,
      CU_TENSOR_MAP_SWIZZLE_128B, CU_TENSOR_MAP_L2_PROMOTION_NONE, CU_TENSOR_MAP_FLOAT_OOB_FILL_NONE);
}
void make_w_map(EncodeFn enc, CUtensorMap* m, void* p, int rows, int cols) {
  cuuint64_t dims[2] = {(cuuint64_t)cols, (cuuint64_t)rows};
  cuuint64_t strides[1] = {(cuuint64_t)cols * 2};
  cuuint32_t box[2] = {32, 32}, es[2] = {1, 1};
  enc(m, CU_TENSOR_MAP_DATA_TYPE_BFLOAT16, 2, p, dims, strides, box, es, CU_TENSOR_MAP_INTERLEAVE_NONE,
      CU_TENSOR_MAP_SWIZZLE_64B, CU_TENSOR_MAP_L2_PROMOTION_NONE, CU_TENSOR_MAP_FLOAT_OOB_FILL_NONE);
}

}

extern "C" void kernel_launch(void* const* d_in, const int* in_sizes, int n_in, void* d_out, int out_size) {
  (void)in_sizes; (void)n_in; (void)out_size;
  void* fn = nullptr;
  cudaDriverEntryPointQueryResult qr;
  cudaGetDriverEntryPoint("cuTensorMapEncodeTiled", &fn, cudaEnableDefault, &qr);
  EncodeFn enc = (EncodeFn)fn;
  Maps maps;
  make_kv_map(enc, &maps.k, d_in[1]);
  make_kv_map(enc, &maps.v, d_in[2]);
  make_w_map(enc, &maps.wq, d_in[3], DM, 4096);
  make_w_map(enc, &maps.wo, d_in[4], 4096, DM);
  make_w_map(enc, &maps.wg, d_in[6], DM, FF);
  make_w_map(enc, &maps.wu, d_in[7], DM, FF);
  make_w_map(enc, &maps.wd, d_in[8], FF, DM);
  cudaFuncSetAttribute(decode_kernel, cudaFuncAttributeMaxDynamicSharedMemorySize, SM_TOTAL);
  decode_kernel<<<NCTA, NTHR, SM_TOTAL, cudaStreamPerThread>>>(
      maps, (const uint32_t*)d_in[0], (const char*)d_in[1], (const char*)d_in[2], (uint32_t*)d_out);
}
```
